```python
import torch

def _softmax(x, axis=-1):
    return torch.softmax(x, dim=axis)
def _gelu(x):
    return torch.nn.functional.gelu(x, approximate="tanh")
def _silu(x):
    return torch.nn.functional.silu(x)
def _sigmoid(x):
    return torch.sigmoid(x)
def _layernorm(x, axis=-1, eps=1e-5):
    m = x.mean(dim=axis, keepdim=True)
    v = x.var(dim=axis, keepdim=True, unbiased=False)
    return (x - m) / torch.sqrt(v + eps)
def _scatter_add(tgt, idx, src, axis=0):
    return tgt.clone().index_add_(axis, idx, src)
def _segment_sum(src, seg, n):
    out = torch.zeros((n,) + src.shape[1:], dtype=src.dtype)
    return out.index_add_(0, seg, src)
def _pad(x, pw):
    flat = tuple(v for pair in reversed(pw) for v in pair)
    return torch.nn.functional.pad(x, flat)

kernel_name = 'gated_mix__linear_kernel_hedgehog__mixer_s_mlp__prompt'

def setup_inputs():

    _w = (lambda a: (lambda t: t.to(torch.bfloat16) if t.is_floating_point() else t)(torch.as_tensor(a)))
    def _A_setup():
        B, S, D, H = 1, 2048, 640, 32
        Dh = D // H
        return {
            "x": _w((lambda *s: torch.randn(*s, dtype=torch.bfloat16) * 0.05)(B, S, D)),
            "wqkv": _w((lambda *s: torch.randn(*s, dtype=torch.bfloat16) * 3.2)(D, 3 * D)),
            "w_phi": _w((lambda *s: torch.randn(*s, dtype=torch.bfloat16) * 3.2)(H, Dh, Dh) * (Dh ** -0.5)),
            "wo": _w((lambda *s: torch.randn(*s, dtype=torch.bfloat16) * 1.6)(D, D)),
        }
    _A_in = _A_setup()

    def _B_setup():
        B, S, D, F = 1, 2048, 640, 1536
        return {
            "x":  _w((lambda *s: torch.randn(*s, dtype=torch.bfloat16) * 0.05)(B, S, D)),
            "w1": _w((lambda *s: torch.randn(*s, dtype=torch.bfloat16) * 3.2)(D, D) * (D ** -0.5)),
            "w2": _w((lambda *s: torch.randn(*s, dtype=torch.bfloat16) * 3.2)(D, D) * (D ** -0.5)),
            "w3": _w((lambda *s: torch.randn(*s, dtype=torch.bfloat16) * 3.2)(D, F) * (D ** -0.5)),
            "w4": _w((lambda *s: torch.randn(*s, dtype=torch.bfloat16) * 3.2)(F, D) * (F ** -0.5)),
        }
    _B_in = _B_setup()

    return {
        "A_x": _A_in["x"],
        "A_wqkv": _A_in["wqkv"],
        "A_w_phi": _A_in["w_phi"],
        "A_wo": _A_in["wo"],
        "B_x": _B_in["x"],
        "B_w1": _B_in["w1"],
        "B_w2": _B_in["w2"],
        "B_w3": _B_in["w3"],
        "B_w4": _B_in["w4"],
        "gate_w": _w((lambda *s: torch.randn(*s, dtype=torch.bfloat16) * 0.05)(640) * 16.0),
    }

def reference(A_x, A_wqkv, A_w_phi, A_wo, B_x, B_w1, B_w2, B_w3, B_w4, gate_w):
    def _A_ref(x, wqkv, w_phi, wo):
        B, S, D = x.shape
        H = 32; Dh = D // H
        qkv = (lambda x, *d: x.permute(*d))((x @ wqkv).reshape(B, S, 3, H, Dh), 2, 0, 3, 1, 4)
        q, k, v = qkv[0], qkv[1], qkv[2]
        pq = torch.einsum("bhsd,hdf->bhsf", q, w_phi)
        pk = torch.einsum("bhsd,hdf->bhsf", k, w_phi)
        phi_q = torch.concatenate([_softmax(pq, axis=-1), _softmax(-pq, axis=-1)], axis=-1)
        phi_k = torch.concatenate([_softmax(pk, axis=-1), _softmax(-pk, axis=-1)], axis=-1)
        kv = torch.einsum("bhsf,bhsd->bhfd", phi_k, v)
        z  = torch.einsum("bhsf->bhf", phi_k)
        num = torch.einsum("bhqf,bhfd->bhqd", phi_q, kv)
        den = torch.einsum("bhqf,bhf->bhq", phi_q, z)[..., None] + 1e-6
        o = num / den
        return (lambda x, *d: x.permute(*d))(o, 0, 2, 1, 3).reshape(B, S, D) @ wo

    def _B_ref(x, w1, w2, w3, w4):
        B, S, D = x.shape
        h = _gelu(_layernorm(x, axis=-1) @ w1)
        c = D // 4
        g0 = _pad(h[:, :, 0*c:1*c], ((0, 0), (1, 0), (0, 0)))[:, :S, :]
        g1 = _pad(h[:, :, 1*c:2*c], ((0, 0), (0, 1), (0, 0)))[:, 1:, :]
        g2 = _pad(h[:, :, 2*c:3*c], ((0, 0), (2, 0), (0, 0)))[:, :S, :]
        g3 = _pad(h[:, :, 3*c:   ], ((0, 0), (0, 2), (0, 0)))[:, 2:, :]
        hs = torch.concatenate([g0, g1, g2, g3], axis=-1) @ w2
        x1 = x + hs
        h2 = _gelu(_layernorm(x1, axis=-1) @ w3) @ w4
        return x1 + h2

    x = A_x
    g = _sigmoid((x * gate_w).sum(-1, keepdims=True))
    a = _A_ref(x, A_wqkv, A_w_phi, A_wo)
    b = _B_ref(x, B_w1, B_w2, B_w3, B_w4)
    return g * a + (1 - g) * b
```

```cpp
#include <cuda_runtime.h>
#include <cuda.h>
#include <cuda_bf16.h>
#include <stdint.h>

typedef __nv_bfloat16 bf16;

constexpr int SEQ = 2048, DM = 640, FF = 1536;
#define PF1_DELAY 800
#define DRY 0
#define H_HOLD 0
#define PF3_DELAY 6500
#define PF4_DELAY 19000
#define PF2_DELAY 4000

__device__ __align__(1024) bf16 g_hs[(SEQ + 2) * DM];
__device__ __align__(1024) bf16 g_x1[SEQ * DM];
__device__ __align__(1024) bf16 g_o[SEQ * DM];
__device__ __align__(1024) bf16 g_h3[SEQ * FF];
__device__ __align__(128) float g_kv[32 * 24 * 40];
__device__ __align__(128) float4 g_st1[4 * SEQ];
__device__ __align__(128) float4 g_xst[26 * 80];
__device__ __align__(128) float g_cs3[FF];
constexpr int FH = 0, FX1 = 26, FST = 42, FKV = 58, FO = 62, FZERO = 78, FDONE = 79, FCS3 = 80, FOZ = 84, FH3 = 85, NFLAG = 181;
#define G4ORD 0x2150743
#define NXTRA 0
__device__ __align__(128) unsigned g_flag[NFLAG * 32];
__device__ unsigned g_epoch;
#define TSARG(x)
#define TS(ev)
#define TSP(ev)

constexpr uint32_t SLOT = 40960;
constexpr uint32_t OFF_AUX = 4 * SLOT;
constexpr uint32_t OFF_PAD = 5 * SLOT;
constexpr uint32_t OFF_W = OFF_PAD + 4096;
constexpr uint32_t OFF_MISC = OFF_W + 20480;
constexpr uint32_t OFF_BAR = OFF_MISC;
constexpr uint32_t OFF_TOK = OFF_MISC + 256;
constexpr uint32_t OFF_CS3 = OFF_MISC + 1536;
constexpr uint32_t OFF_GATE = OFF_MISC + 2432;
constexpr uint32_t OFF_ROLE = OFF_MISC + 3008;
constexpr uint32_t SMEM_BYTES = OFF_MISC + 3072;
constexpr uint32_t B_FULL = 0, B_EMPTY = 40, B_XRES = 80, B_WPHI = 88, B_ST3 = 96, B_JOB0 = 104, B_JOB1 = 112, B_AUXF = 120, B_WFREE = 128,
                   B_SF1 = 136, B_RDY = 144,  B_DEP = 192, B_FIN = 224, B_KV = 248, B_DEP2 = 3024  , B_PHI = 2944  ;

enum { M_XA, M_XT, M_XR, M_W1, M_WQKV, M_W2, M_W3, M_WO, M_W4, M_HSST, M_HSA, M_X1ST, M_X1A, M_H3ST, M_H3A, M_OST, M_OA, M_OUT, NMAPS };
struct Params {
  CUtensorMap m[NMAPS];
  bf16* out;
  const bf16 *x, *wqkv, *wphi, *wo, *w1, *w2, *w3, *w4, *gatew;
};

__device__ __forceinline__ uint32_t smem_u32(const void* p) { return (uint32_t)__cvta_generic_to_shared(p); }
__device__ __forceinline__ void mbar_init(uint32_t bar, int cnt) { asm volatile("mbarrier.init.shared::cta.b64 [%0], %1;" ::"r"(bar), "r"(cnt)); }
__device__ __forceinline__ void mbar_expect_tx(uint32_t bar, uint32_t bytes) {
  asm volatile("mbarrier.arrive.expect_tx.shared::cta.b64 _, [%0], %1;" ::"r"(bar), "r"(bytes) : "memory");
}
__device__ __forceinline__ void mbar_arrive(uint32_t bar, uint32_t cnt) {
  asm volatile("mbarrier.arrive.shared::cta.b64 _, [%0], %1;" ::"r"(bar), "r"(cnt) : "memory");
}
__device__ __forceinline__ void mbar_arrive_remote(uint32_t bar, uint32_t cta, uint32_t cnt) {
  asm volatile("{\n.reg .b32 ra;\nmapa.shared::cluster.u32 ra, %0, %1;\nmbarrier.arrive.shared::cluster.b64 _, [ra], %2;\n}\n" ::"r"(bar), "r"(cta), "r"(cnt) : "memory");
}
__device__ __forceinline__ uint32_t mbar_try(uint32_t bar, uint32_t parity) {
  uint32_t ok;
  asm volatile("{\n.reg .pred p;\nmbarrier.try_wait.parity.shared::cta.b64 p, [%1], %2;\nselp.u32 %0, 1, 0, p;\n}\n" : "=r"(ok) : "r"(bar), "r"(parity) : "memory");
  return ok;
}
__device__ __forceinline__ uint32_t mbar_try_t(uint32_t bar, uint32_t parity, uint32_t ns) {
  uint32_t ok;
  asm volatile("{\n.reg .pred p;\nmbarrier.try_wait.parity.shared::cta.b64 p, [%1], %2, %3;\nselp.u32 %0, 1, 0, p;\n}\n" : "=r"(ok) : "r"(bar), "r"(parity), "r"(ns) : "memory");
  return ok;
}
__device__ __forceinline__ uint32_t mbar_test(uint32_t bar, uint32_t parity) {
  uint32_t ok;
  asm volatile("{\n.reg .pred p;\nmbarrier.test_wait.parity.shared::cta.b64 p, [%1], %2;\nselp.u32 %0, 1, 0, p;\n}\n" : "=r"(ok) : "r"(bar), "r"(parity) : "memory");
  return ok;
}
constexpr int SPIN_LIMIT = 1 << 16;
constexpr uint32_t WAIT_CYCLES = 1u << 25;
__device__ __forceinline__ int fresh_tid() {
  int t;
  asm volatile("mov.u32 %0, %%tid.x;" : "=r"(t));
  return t;
}
__device__ __forceinline__ uint32_t clock32() {
  uint32_t c;
  asm volatile("mov.u32 %0, %%clock;" : "=r"(c));
  return c;
}
__device__ __forceinline__ void mbar_wait(uint32_t bar, uint32_t parity) {
  asm volatile(
      "{\n.reg .pred p;\n.reg .u32 n;\nmov.u32 n, 0;\n"
      "W_%=:\nmbarrier.try_wait.parity.shared::cta.b64 p, [%0], %1;\n"
      "add.u32 n, n, 1;\n@p bra D_%=;\nsetp.lt.u32 p, n, 0x40000;\n@p bra W_%=;\nD_%=:\n}\n" ::"r"(bar), "r"(parity) : "memory");
}
__device__ __forceinline__ void tma2d(uint32_t dst, const CUtensorMap* tm, uint32_t bar, int c0, int c1) {
  asm volatile("cp.async.bulk.tensor.2d.shared::cluster.global.mbarrier::complete_tx::bytes [%0], [%1, {%3, %4}], [%2];" ::"r"(dst), "l"(tm), "r"(bar), "r"(c0), "r"(c1) : "memory");
}
__device__ __forceinline__ void tma3d(uint32_t dst, const CUtensorMap* tm, uint32_t bar, int c0, int c1, int c2) {
  asm volatile("cp.async.bulk.tensor.3d.shared::cluster.global.mbarrier::complete_tx::bytes [%0], [%1, {%3, %4, %5}], [%2];" ::"r"(dst), "l"(tm), "r"(bar), "r"(c0), "r"(c1), "r"(c2) : "memory");
}
__device__ __forceinline__ void tma3d_mc(uint32_t dst, const CUtensorMap* tm, uint32_t bar, int c0, int c1, int c2, uint16_t mask) {
  asm volatile("cp.async.bulk.tensor.3d.shared::cluster.global.mbarrier::complete_tx::bytes.multicast::cluster [%0], [%1, {%3, %4, %5}], [%2], %6;" ::"r"(dst), "l"(tm), "r"(bar), "r"(c0), "r"(c1), "r"(c2), "h"(mask) : "memory");
}
__device__ __forceinline__ void tma_st2d(const CUtensorMap* tm, uint32_t src, int c0, int c1) {
  asm volatile("cp.async.bulk.tensor.2d.global.shared::cta.bulk_group [%0, {%2, %3}], [%1];" ::"l"(tm), "r"(src), "r"(c0), "r"(c1) : "memory");
}
__device__ __forceinline__ void tma_st3d(const CUtensorMap* tm, uint32_t src, int c0, int c1, int c2) {
  asm volatile("cp.async.bulk.tensor.3d.global.shared::cta.bulk_group [%0, {%2, %3, %4}], [%1];" ::"l"(tm), "r"(src), "r"(c0), "r"(c1), "r"(c2) : "memory");
}
__device__ __forceinline__ void bulk_load(uint32_t dst, const void* src, uint32_t bytes, uint32_t bar) {
  asm volatile("cp.async.bulk.shared::cluster.global.mbarrier::complete_tx::bytes [%0], [%1], %2, [%3];" ::"r"(dst), "l"(src), "r"(bytes), "r"(bar) : "memory");
}
__device__ __forceinline__ void bulk_reduce(float* dst, uint32_t src, uint32_t bytes) {
  asm volatile("cp.reduce.async.bulk.global.shared::cta.bulk_group.add.f32 [%0], [%1], %2;" ::"l"(dst), "r"(src), "r"(bytes) : "memory");
}
__device__ __forceinline__ void bulk_commit() { asm volatile("cp.async.bulk.commit_group;" ::: "memory"); }
__device__ __forceinline__ void bulk_wait0() { asm volatile("cp.async.bulk.wait_group 0;" ::: "memory"); }
__device__ __forceinline__ void bulk_wait0_read() { asm volatile("cp.async.bulk.wait_group.read 0;" ::: "memory"); }
__device__ __forceinline__ void l2_prefetch(const void* p, uint32_t bytes) {
  asm volatile("cp.async.bulk.prefetch.L2.global [%0], %1;" ::"l"(p), "r"(bytes) : "memory");
}
__device__ __forceinline__ void prefetch_map(const CUtensorMap* tm) { asm volatile("prefetch.tensormap [%0];" ::"l"(tm) : "memory"); }
__device__ __forceinline__ void fence_async_smem() { asm volatile("fence.proxy.async.shared::cta;" ::: "memory"); }
__device__ __forceinline__ void fence_async_global() { asm volatile("fence.proxy.async.global;" ::: "memory"); }
__device__ __forceinline__ void bar_sync(int id, int n) { asm volatile("bar.sync %0, %1;" ::"r"(id), "r"(n) : "memory"); }
__device__ __forceinline__ void bar_arrive(int id, int n) { asm volatile("bar.arrive %0, %1;" ::"r"(id), "r"(n) : "memory"); }
__device__ __forceinline__ unsigned ld_flag(const unsigned* p) {
  unsigned v;
  asm volatile("ld.relaxed.gpu.global.u32 %0, [%1];" : "=r"(v) : "l"(p) : "memory");
  return v;
}
__device__ __forceinline__ void flag_add_release(int idx) {
  asm volatile("red.release.gpu.global.add.u32 [%0], 1;" ::"l"(&g_flag[idx * 32]) : "memory");
}
__device__ __forceinline__ void flag_add(int idx) {
  asm volatile("red.relaxed.gpu.global.add.u32 [%0], 1;" ::"l"(&g_flag[idx * 32]) : "memory");
}
__device__ __forceinline__ void fence_acquire() { asm volatile("fence.acq_rel.gpu;" ::: "memory"); }
__device__ __forceinline__ void flag_wait(int idx, unsigned target) {
  int it = 0;
  while (ld_flag(&g_flag[idx * 32]) < target && ++it < SPIN_LIMIT) {
  }
}
__device__ __forceinline__ uint64_t mk_desc(uint32_t a16, uint32_t off, uint32_t lbo, uint32_t sbo, uint32_t swz) {
  uint64_t d;
  asm("mov.b64 %0, {%1, %2};" : "=l"(d) : "r"(a16 + ((off >> 4) | ((lbo >> 4) << 16))), "r"((sbo >> 4) | (swz << 30)));
  return d;
}
#define WG_FENCE() asm volatile("wgmma.fence.sync.aligned;" ::: "memory")
#define WG_COMMIT() asm volatile("wgmma.commit_group.sync.aligned;" ::: "memory")
#define WG_WAIT(n) asm volatile("wgmma.wait_group.sync.aligned %0;" ::"n"(n) : "memory")
template <int N>
__device__ __forceinline__ void reg_fence(float (&a)[N]) {
#pragma unroll
  for (int i = 0; i < N; i++) asm volatile("" : "+f"(a[i])::"memory");
}
template <int N>
__device__ __forceinline__ void reg_fence_u(uint32_t (&a)[N]) {
#pragma unroll
  for (int i = 0; i < N; i++) asm volatile("" : "+r"(a[i])::"memory");
}
__device__ __forceinline__ uint32_t pack2(float lo, float hi) {
  uint32_t r;
  asm("cvt.rn.bf16x2.f32 %0, %1, %2;" : "=r"(r) : "f"(hi), "f"(lo));
  return r;
}
__device__ __forceinline__ float bf_lo(uint32_t v) { return __uint_as_float(v << 16); }
__device__ __forceinline__ float bf_hi(uint32_t v) { return __uint_as_float(v & 0xffff0000u); }
__device__ __forceinline__ void stsm4(uint32_t addr, uint32_t r0, uint32_t r1, uint32_t r2, uint32_t r3) {
  asm volatile("stmatrix.sync.aligned.m8n8.x4.shared.b16 [%0], {%1, %2, %3, %4};" ::"r"(addr), "r"(r0), "r"(r1), "r"(r2), "r"(r3) : "memory");
}
__device__ __forceinline__ void stsm4t(uint32_t addr, uint32_t r0, uint32_t r1, uint32_t r2, uint32_t r3) {
  asm volatile("stmatrix.sync.aligned.m8n8.x4.trans.shared.b16 [%0], {%1, %2, %3, %4};" ::"r"(addr), "r"(r0), "r"(r1), "r"(r2), "r"(r3) : "memory");
}
__device__ __forceinline__ void stsm2(uint32_t addr, uint32_t r0, uint32_t r1) {
  asm volatile("stmatrix.sync.aligned.m8n8.x2.shared.b16 [%0], {%1, %2};" ::"r"(addr), "r"(r0), "r"(r1) : "memory");
}
__device__ __forceinline__ void ldsm4(uint32_t addr, uint32_t& r0, uint32_t& r1, uint32_t& r2, uint32_t& r3) {
  asm volatile("ldmatrix.sync.aligned.m8n8.x4.shared.b16 {%0, %1, %2, %3}, [%4];" : "=r"(r0), "=r"(r1), "=r"(r2), "=r"(r3) : "r"(addr) : "memory");
}
__device__ __forceinline__ void ldsm4t(uint32_t addr, uint32_t& r0, uint32_t& r1, uint32_t& r2, uint32_t& r3) {
  asm volatile("ldmatrix.sync.aligned.m8n8.x4.trans.shared.b16 {%0, %1, %2, %3}, [%4];" : "=r"(r0), "=r"(r1), "=r"(r2), "=r"(r3) : "r"(addr) : "memory");
}
__device__ __forceinline__ float4 lds128f(uint32_t addr) {
  float4 v;
  asm volatile("ld.shared.v4.f32 {%0, %1, %2, %3}, [%4];" : "=f"(v.x), "=f"(v.y), "=f"(v.z), "=f"(v.w) : "r"(addr) : "memory");
  return v;
}
__device__ __forceinline__ float2 lds64f(uint32_t addr) {
  float2 v;
  asm volatile("ld.shared.v2.f32 {%0, %1}, [%2];" : "=f"(v.x), "=f"(v.y) : "r"(addr) : "memory");
  return v;
}
__device__ __forceinline__ float lds32f(uint32_t addr) {
  float v;
  asm volatile("ld.shared.f32 %0, [%1];" : "=f"(v) : "r"(addr) : "memory");
  return v;
}
__device__ __forceinline__ uint4 lds128u(uint32_t addr) {
  uint4 v;
  asm volatile("ld.shared.v4.u32 {%0, %1, %2, %3}, [%4];" : "=r"(v.x), "=r"(v.y), "=r"(v.z), "=r"(v.w) : "r"(addr) : "memory");
  return v;
}
__device__ __forceinline__ void sts128u(uint32_t addr, uint32_t a, uint32_t b, uint32_t c, uint32_t d) {
  asm volatile("st.shared.v4.u32 [%0], {%1, %2, %3, %4};" ::"r"(addr), "r"(a), "r"(b), "r"(c), "r"(d) : "memory");
}
__device__ __forceinline__ void sts128f(uint32_t addr, float a, float b, float c, float d) {
  asm volatile("st.shared.v4.f32 [%0], {%1, %2, %3, %4};" ::"r"(addr), "f"(a), "f"(b), "f"(c), "f"(d) : "memory");
}
__device__ __forceinline__ void sts64f(uint32_t addr, float a, float b) {
  asm volatile("st.shared.v2.f32 [%0], {%1, %2};" ::"r"(addr), "f"(a), "f"(b) : "memory");
}
__device__ __forceinline__ void sts64u(uint32_t addr, uint32_t a, uint32_t b) {
  asm volatile("st.shared.v2.u32 [%0], {%1, %2};" ::"r"(addr), "r"(a), "r"(b) : "memory");
}
__device__ __forceinline__ void sts32f(uint32_t addr, float a) { asm volatile("st.shared.f32 [%0], %1;" ::"r"(addr), "f"(a) : "memory"); }
__device__ __forceinline__ float4 ldg_cg128(const float* p) {
  float4 v;
  asm volatile("ld.global.cg.v4.f32 {%0, %1, %2, %3}, [%4];" : "=f"(v.x), "=f"(v.y), "=f"(v.z), "=f"(v.w) : "l"(p) : "memory");
  return v;
}
__device__ __forceinline__ float epoch_tag() { return __uint_as_float((ld_flag(&g_epoch) & 0xFFFFFF) + 1); }
__device__ __forceinline__ bool tag_ok(const float4& v, float tag) { return __float_as_uint(v.w) == __float_as_uint(tag); }
__device__ __forceinline__ float4 ld_poll128(const void* p) {
  float4 v;
  asm volatile("ld.relaxed.gpu.global.v4.f32 {%0, %1, %2, %3}, [%4];" : "=f"(v.x), "=f"(v.y), "=f"(v.z), "=f"(v.w) : "l"(p) : "memory");
  return v;
}
__device__ __forceinline__ float2 ldg_cg64(const float* p) {
  float2 v;
  asm volatile("ld.global.cg.v2.f32 {%0, %1}, [%2];" : "=f"(v.x), "=f"(v.y) : "l"(p) : "memory");
  return v;
}
__device__ __forceinline__ void red_add2(float* p, float a, float b) {
  asm volatile("red.global.add.v2.f32 [%0], {%1, %2};" ::"l"(p), "f"(a), "f"(b) : "memory");
}
__device__ __forceinline__ float ex2f(float x) {
  float r;
  asm("ex2.approx.ftz.f32 %0, %1;" : "=f"(r) : "f"(x));
  return r;
}
__device__ __forceinline__ float tanhf_(float x) {
  float r;
  asm("tanh.approx.f32 %0, %1;" : "=f"(r) : "f"(x));
  return r;
}
__device__ __forceinline__ float rcpf_(float x) {
  float r;
  asm("rcp.approx.ftz.f32 %0, %1;" : "=f"(r) : "f"(x));
  return r;
}
__device__ __forceinline__ float fmul_keep(float x) {
  float r;
  asm volatile("mul.f32 %0, %1, 0f3FB8AA3B;" : "=f"(r) : "f"(x));
  return r;
}
__device__ __forceinline__ float gelu_s(float t, float c1, float c2, float hr) {
  float u = t * fmaf(t * t, c2, c1);
  float h = t * hr;
  return fmaf(h, tanhf_(u), h);
}
constexpr float GK1 = 0.7978845608028654f, GK2 = 0.7978845608028654f * 0.044715f, LOG2E = 1.4426950408889634f;

__device__ __forceinline__ void wg_t88(float (&d)[44], uint64_t da, uint64_t db, int sd) {
  asm volatile("{\n.reg .pred p;\n"
    "setp.ne.b32 p, %46, 0;\n"
    "wgmma.mma_async.sync.aligned.m64n88k16.f32.bf16.bf16 "
    "{%0, %1, %2, %3, %4, %5, %6, %7, %8, %9, %10, %11, %12, %13, %14, %15, "
    "%16, %17, %18, %19, %20, %21, %22, %23, %24, %25, %26, %27, %28, %29, %30, %31, "
    "%32, %33, %34, %35, %36, %37, %38, %39, %40, %41, %42, %43}, "
    "%44, %45, p, 1, 1, 1, 0;\n}\n"
    : "+f"(d[0]), "+f"(d[1]), "+f"(d[2]), "+f"(d[3]), "+f"(d[4]), "+f"(d[5]), "+f"(d[6]), "+f"(d[7]),
      "+f"(d[8]), "+f"(d[9]), "+f"(d[10]), "+f"(d[11]), "+f"(d[12]), "+f"(d[13]), "+f"(d[14]), "+f"(d[15]),
      "+f"(d[16]), "+f"(d[17]), "+f"(d[18]), "+f"(d[19]), "+f"(d[20]), "+f"(d[21]), "+f"(d[22]), "+f"(d[23]),
      "+f"(d[24]), "+f"(d[25]), "+f"(d[26]), "+f"(d[27]), "+f"(d[28]), "+f"(d[29]), "+f"(d[30]), "+f"(d[31]),
      "+f"(d[32]), "+f"(d[33]), "+f"(d[34]), "+f"(d[35]), "+f"(d[36]), "+f"(d[37]), "+f"(d[38]), "+f"(d[39]),
      "+f"(d[40]), "+f"(d[41]), "+f"(d[42]), "+f"(d[43])
    : "l"(da), "l"(db), "r"(sd));
}
__device__ __forceinline__ void wg_n160(float (&d)[80], uint64_t da, uint64_t db, int sd) {
  asm volatile("{\n.reg .pred p;\n"
    "setp.ne.b32 p, %82, 0;\n"
    "wgmma.mma_async.sync.aligned.m64n160k16.f32.bf16.bf16 "
    "{%0, %1, %2, %3, %4, %5, %6, %7, %8, %9, %10, %11, %12, %13, %14, %15, "
    "%16, %17, %18, %19, %20, %21, %22, %23, %24, %25, %26, %27, %28, %29, %30, %31, "
    "%32, %33, %34, %35, %36, %37, %38, %39, %40, %41, %42, %43, %44, %45, %46, %47, "
    "%48, %49, %50, %51, %52, %53, %54, %55, %56, %57, %58, %59, %60, %61, %62, %63, "
    "%64, %65, %66, %67, %68, %69, %70, %71, %72, %73, %74, %75, %76, %77, %78, %79}, "
    "%80, %81, p, 1, 1, 0, 1;\n}\n"
    : "+f"(d[0]), "+f"(d[1]), "+f"(d[2]), "+f"(d[3]), "+f"(d[4]), "+f"(d[5]), "+f"(d[6]), "+f"(d[7]),
      "+f"(d[8]), "+f"(d[9]), "+f"(d[10]), "+f"(d[11]), "+f"(d[12]), "+f"(d[13]), "+f"(d[14]), "+f"(d[15]),
      "+f"(d[16]), "+f"(d[17]), "+f"(d[18]), "+f"(d[19]), "+f"(d[20]), "+f"(d[21]), "+f"(d[22]), "+f"(d[23]),
      "+f"(d[24]), "+f"(d[25]), "+f"(d[26]), "+f"(d[27]), "+f"(d[28]), "+f"(d[29]), "+f"(d[30]), "+f"(d[31]),
      "+f"(d[32]), "+f"(d[33]), "+f"(d[34]), "+f"(d[35]), "+f"(d[36]), "+f"(d[37]), "+f"(d[38]), "+f"(d[39]),
      "+f"(d[40]), "+f"(d[41]), "+f"(d[42]), "+f"(d[43]), "+f"(d[44]), "+f"(d[45]), "+f"(d[46]), "+f"(d[47]),
      "+f"(d[48]), "+f"(d[49]), "+f"(d[50]), "+f"(d[51]), "+f"(d[52]), "+f"(d[53]), "+f"(d[54]), "+f"(d[55]),
      "+f"(d[56]), "+f"(d[57]), "+f"(d[58]), "+f"(d[59]), "+f"(d[60]), "+f"(d[61]), "+f"(d[62]), "+f"(d[63]),
      "+f"(d[64]), "+f"(d[65]), "+f"(d[66]), "+f"(d[67]), "+f"(d[68]), "+f"(d[69]), "+f"(d[70]), "+f"(d[71]),
      "+f"(d[72]), "+f"(d[73]), "+f"(d[74]), "+f"(d[75]), "+f"(d[76]), "+f"(d[77]), "+f"(d[78]), "+f"(d[79])
    : "l"(da), "l"(db), "r"(sd));
}
__device__ __forceinline__ void wg_n192(float (&d)[96], uint64_t da, uint64_t db, int sd) {
  asm volatile("{\n.reg .pred p;\n"
    "setp.ne.b32 p, %98, 0;\n"
    "wgmma.mma_async.sync.aligned.m64n192k16.f32.bf16.bf16 "
    "{%0, %1, %2, %3, %4, %5, %6, %7, %8, %9, %10, %11, %12, %13, %14, %15, "
    "%16, %17, %18, %19, %20, %21, %22, %23, %24, %25, %26, %27, %28, %29, %30, %31, "
    "%32, %33, %34, %35, %36, %37, %38, %39, %40, %41, %42, %43, %44, %45, %46, %47, "
    "%48, %49, %50, %51, %52, %53, %54, %55, %56, %57, %58, %59, %60, %61, %62, %63, "
    "%64, %65, %66, %67, %68, %69, %70, %71, %72, %73, %74, %75, %76, %77, %78, %79, "
    "%80, %81, %82, %83, %84, %85, %86, %87, %88, %89, %90, %91, %92, %93, %94, %95}, "
    "%96, %97, p, 1, 1, 0, 1;\n}\n"
    : "+f"(d[0]), "+f"(d[1]), "+f"(d[2]), "+f"(d[3]), "+f"(d[4]), "+f"(d[5]), "+f"(d[6]), "+f"(d[7]),
      "+f"(d[8]), "+f"(d[9]), "+f"(d[10]), "+f"(d[11]), "+f"(d[12]), "+f"(d[13]), "+f"(d[14]), "+f"(d[15]),
      "+f"(d[16]), "+f"(d[17]), "+f"(d[18]), "+f"(d[19]), "+f"(d[20]), "+f"(d[21]), "+f"(d[22]), "+f"(d[23]),
      "+f"(d[24]), "+f"(d[25]), "+f"(d[26]), "+f"(d[27]), "+f"(d[28]), "+f"(d[29]), "+f"(d[30]), "+f"(d[31]),
      "+f"(d[32]), "+f"(d[33]), "+f"(d[34]), "+f"(d[35]), "+f"(d[36]), "+f"(d[37]), "+f"(d[38]), "+f"(d[39]),
      "+f"(d[40]), "+f"(d[41]), "+f"(d[42]), "+f"(d[43]), "+f"(d[44]), "+f"(d[45]), "+f"(d[46]), "+f"(d[47]),
      "+f"(d[48]), "+f"(d[49]), "+f"(d[50]), "+f"(d[51]), "+f"(d[52]), "+f"(d[53]), "+f"(d[54]), "+f"(d[55]),
      "+f"(d[56]), "+f"(d[57]), "+f"(d[58]), "+f"(d[59]), "+f"(d[60]), "+f"(d[61]), "+f"(d[62]), "+f"(d[63]),
      "+f"(d[64]), "+f"(d[65]), "+f"(d[66]), "+f"(d[67]), "+f"(d[68]), "+f"(d[69]), "+f"(d[70]), "+f"(d[71]),
      "+f"(d[72]), "+f"(d[73]), "+f"(d[74]), "+f"(d[75]), "+f"(d[76]), "+f"(d[77]), "+f"(d[78]), "+f"(d[79]),
      "+f"(d[80]), "+f"(d[81]), "+f"(d[82]), "+f"(d[83]), "+f"(d[84]), "+f"(d[85]), "+f"(d[86]), "+f"(d[87]),
      "+f"(d[88]), "+f"(d[89]), "+f"(d[90]), "+f"(d[91]), "+f"(d[92]), "+f"(d[93]), "+f"(d[94]), "+f"(d[95])
    : "l"(da), "l"(db), "r"(sd));
}
__device__ __forceinline__ void wg_rs40(float (&d)[20], uint32_t a0, uint32_t a1, uint32_t a2, uint32_t a3, uint64_t db, int sd) {
  asm volatile("{\n.reg .pred p;\n"
    "setp.ne.b32 p, %25, 0;\n"
    "wgmma.mma_async.sync.aligned.m64n40k16.f32.bf16.bf16 "
    "{%0, %1, %2, %3, %4, %5, %6, %7, %8, %9, %10, %11, %12, %13, %14, %15, "
    "%16, %17, %18, %19}, "
    "{%20, %21, %22, %23}, %24, p, 1, 1, 1;\n}\n"
    : "+f"(d[0]), "+f"(d[1]), "+f"(d[2]), "+f"(d[3]), "+f"(d[4]), "+f"(d[5]), "+f"(d[6]), "+f"(d[7]),
      "+f"(d[8]), "+f"(d[9]), "+f"(d[10]), "+f"(d[11]), "+f"(d[12]), "+f"(d[13]), "+f"(d[14]), "+f"(d[15]),
      "+f"(d[16]), "+f"(d[17]), "+f"(d[18]), "+f"(d[19])
    : "r"(a0), "r"(a1), "r"(a2), "r"(a3), "l"(db), "r"(sd));
}
__device__ __forceinline__ void wg_rs48(float (&d)[24], uint32_t a0, uint32_t a1, uint32_t a2, uint32_t a3, uint64_t db, int sd) {
  asm volatile("{\n.reg .pred p;\n"
    "setp.ne.b32 p, %29, 0;\n"
    "wgmma.mma_async.sync.aligned.m64n48k16.f32.bf16.bf16 "
    "{%0, %1, %2, %3, %4, %5, %6, %7, %8, %9, %10, %11, %12, %13, %14, %15, "
    "%16, %17, %18, %19, %20, %21, %22, %23}, "
    "{%24, %25, %26, %27}, %28, p, 1, 1, 0;\n}\n"
    : "+f"(d[0]), "+f"(d[1]), "+f"(d[2]), "+f"(d[3]), "+f"(d[4]), "+f"(d[5]), "+f"(d[6]), "+f"(d[7]),
      "+f"(d[8]), "+f"(d[9]), "+f"(d[10]), "+f"(d[11]), "+f"(d[12]), "+f"(d[13]), "+f"(d[14]), "+f"(d[15]),
      "+f"(d[16]), "+f"(d[17]), "+f"(d[18]), "+f"(d[19]), "+f"(d[20]), "+f"(d[21]), "+f"(d[22]), "+f"(d[23])
    : "r"(a0), "r"(a1), "r"(a2), "r"(a3), "l"(db), "r"(sd));
}
__device__ __forceinline__ void wg_tt80(float (&d)[40], uint64_t da, uint64_t db, int sd) {
  asm volatile("{\n.reg .pred p;\n"
    "setp.ne.b32 p, %42, 0;\n"
    "wgmma.mma_async.sync.aligned.m64n80k16.f32.bf16.bf16 "
    "{%0, %1, %2, %3, %4, %5, %6, %7, %8, %9, %10, %11, %12, %13, %14, %15, "
    "%16, %17, %18, %19, %20, %21, %22, %23, %24, %25, %26, %27, %28, %29, %30, %31, "
    "%32, %33, %34, %35, %36, %37, %38, %39}, "
    "%40, %41, p, 1, 1, 1, 1;\n}\n"
    : "+f"(d[0]), "+f"(d[1]), "+f"(d[2]), "+f"(d[3]), "+f"(d[4]), "+f"(d[5]), "+f"(d[6]), "+f"(d[7]),
      "+f"(d[8]), "+f"(d[9]), "+f"(d[10]), "+f"(d[11]), "+f"(d[12]), "+f"(d[13]), "+f"(d[14]), "+f"(d[15]),
      "+f"(d[16]), "+f"(d[17]), "+f"(d[18]), "+f"(d[19]), "+f"(d[20]), "+f"(d[21]), "+f"(d[22]), "+f"(d[23]),
      "+f"(d[24]), "+f"(d[25]), "+f"(d[26]), "+f"(d[27]), "+f"(d[28]), "+f"(d[29]), "+f"(d[30]), "+f"(d[31]),
      "+f"(d[32]), "+f"(d[33]), "+f"(d[34]), "+f"(d[35]), "+f"(d[36]), "+f"(d[37]), "+f"(d[38]), "+f"(d[39])
    : "l"(da), "l"(db), "r"(sd));
}

enum { NB_WG0 = 1, NB_WG1 = 2, NB_ORD0 = 3, NB_ORD1 = 4, NB_V = 5, NB_STAT = 6, NB_VM = 7 };

__device__ __forceinline__ void release_slot(uint32_t bar, bool mc, uint32_t peer, uint32_t units) {
  if (mc) {
    mbar_arrive(bar, units >> 1);
    mbar_arrive_remote(bar, peer, units >> 1);
  } else {
    mbar_arrive(bar, units);
  }
}
__device__ __forceinline__ void signal_tile(uint32_t bar, int lane) {
  fence_async_smem();
  __syncwarp();
  if (lane == 0) mbar_arrive(bar, 1);
}

__device__ __forceinline__ void half_kblock(float (&acc)[80], uint32_t sa, int m) {
#pragma unroll
  for (int k = 0; k < 4; k++)
    wg_n160(acc, mk_desc(sa, m * 8192 + k * 32, 16, 1024, 1), mk_desc(sa, 16384 + (k >> 1) * 10240 + (k & 1) * 1024, 2048, 512, 2), 1);
}
template <bool STAG, class Epi>
__device__ __forceinline__ void main_n160(float (&acc)[2][80], uint32_t sb, int n, int s, uint32_t par, uint32_t nxt, bool zero, int hold, uint32_t peer,
                                          bool elect, Epi epi
) {
  int prev = 0;
#pragma unroll 1
  for (int kb = 0; kb < (STAG ? n - 3 : n); kb++) {
    const uint32_t sa = ((sb & 0x3FFFF) + s * SLOT) >> 4;
    TS(ts0 + 2 * kb);
    mbar_wait(sb + OFF_BAR + B_FULL + 8 * s, (par >> s) & 1);
    TS(ts0 + 1 + 2 * kb);
    WG_FENCE();
#pragma unroll
    for (int k = 0; k < 4; k++) {
      const uint64_t db = mk_desc(sa, 16384 + (k >> 1) * 10240 + (k & 1) * 1024, 2048, 512, 2);
#pragma unroll
      for (int m = 0; m < 2; m++) wg_n160(acc[m], mk_desc(sa, m * 8192 + k * 32, 16, 1024, 1), db, (k > 0 || kb > 0 || !zero) ? 1 : 0);
    }
    WG_COMMIT();
    WG_WAIT(1);
    if (kb > 0 && kb + hold <= n && elect) release_slot(sb + OFF_BAR + B_EMPTY + 8 * prev, true, peer, 16);
    prev = s;
    par ^= 1u << s;
    s = (nxt >> (4 * s)) & 7;
  }
  if (STAG) {
    const int s1 = (nxt >> (4 * s)) & 7, s2 = (nxt >> (4 * s1)) & 7;
    const uint32_t a0 = ((sb & 0x3FFFF) + s * SLOT) >> 4, a1 = ((sb & 0x3FFFF) + s1 * SLOT) >> 4, a2 = ((sb & 0x3FFFF) + s2 * SLOT) >> 4;
    mbar_wait(sb + OFF_BAR + B_FULL + 8 * s, (par >> s) & 1);
    WG_FENCE();
    half_kblock(acc[0], a0, 0);
    mbar_wait(sb + OFF_BAR + B_FULL + 8 * s1, (par >> s1) & 1);
    half_kblock(acc[0], a1, 0);
    mbar_wait(sb + OFF_BAR + B_FULL + 8 * s2, (par >> s2) & 1);
    half_kblock(acc[0], a2, 0);
    WG_COMMIT();
    half_kblock(acc[1], a0, 1);
    WG_COMMIT();
    WG_WAIT(1);
    reg_fence(acc[0]);
    epi(0);
    WG_FENCE();
    half_kblock(acc[1], a1, 1);
    half_kblock(acc[1], a2, 1);
    WG_COMMIT();
    WG_WAIT(0);
    reg_fence(acc[1]);
    if (elect && hold < 4) {
      release_slot(sb + OFF_BAR + B_EMPTY + 8 * prev, true, peer, 16);
      release_slot(sb + OFF_BAR + B_EMPTY + 8 * s, true, peer, 16);
      if (hold == 0) { release_slot(sb + OFF_BAR + B_EMPTY + 8 * s1, true, peer, 16); release_slot(sb + OFF_BAR + B_EMPTY + 8 * s2, true, peer, 16); }
    }
    epi(1);
  } else {
    WG_WAIT(0);
    reg_fence(acc[0]);
    reg_fence(acc[1]);
    if (elect && hold == 0) release_slot(sb + OFF_BAR + B_EMPTY + 8 * prev, true, peer, 16);
  }
}

__device__ __forceinline__ void p_issue(float (&p0)[20], float (&p1)[20], float (&p2)[20], float (&p3)[20], uint32_t (&af)[40], uint32_t sb, int ord_id) {
  WG_FENCE();
#pragma unroll
  for (int s = 0; s < 3; s++) {
    wg_rs40(p0, af[4 * s], af[4 * s + 1], af[4 * s + 2], af[4 * s + 3], mk_desc((sb & 0x3FFFF) >> 4, OFF_W + s * 1280, 128, 256, 0), s > 0);
    wg_rs40(p1, af[4 * s + 8], af[4 * s + 9], af[4 * s + 10], af[4 * s + 11], mk_desc((sb & 0x3FFFF) >> 4, OFF_W + (3 + s) * 1280, 128, 256, 0), s > 0);
    wg_rs40(p2, af[4 * s + 20], af[4 * s + 21], af[4 * s + 22], af[4 * s + 23], mk_desc((sb & 0x3FFFF) >> 4, OFF_W + (6 + s) * 1280, 128, 256, 0), s > 0);
    wg_rs40(p3, af[4 * s + 28], af[4 * s + 29], af[4 * s + 30], af[4 * s + 31], mk_desc((sb & 0x3FFFF) >> 4, OFF_W + (9 + s) * 1280, 128, 256, 0), s > 0);
  }
  WG_COMMIT();
  if (ord_id >= 0) bar_arrive(ord_id, 256);
  WG_WAIT(0);
  reg_fence(p0); reg_fence(p1); reg_fence(p2); reg_fence(p3);
}
template <bool GUARD, int HH>
__device__ __forceinline__ void sm_exp(float (&e)[20], const float (&pd)[20]) {
  float mx = 0.f, mn = 0.f;
  if (GUARD) {
    mx = fmaxf(pd[2 * HH], pd[2 * HH + 1]); mn = fminf(pd[2 * HH], pd[2 * HH + 1]);
#pragma unroll
    for (int j = 1; j < 5; j++) {
      mx = fmaxf(mx, fmaxf(pd[4 * j + 2 * HH], pd[4 * j + 2 * HH + 1]));
      mn = fminf(mn, fminf(pd[4 * j + 2 * HH], pd[4 * j + 2 * HH + 1]));
    }
    mx = fmaxf(mx, __shfl_xor_sync(0xffffffffu, mx, 1));
    mn = fminf(mn, __shfl_xor_sync(0xffffffffu, mn, 1));
  }
#pragma unroll
  for (int i = 0; i < 10; i++) {
    const float v = pd[4 * (i >> 1) + 2 * HH + (i & 1)];
    e[i] = ex2f(GUARD ? v - mx : v);
    e[10 + i] = ex2f(GUARD ? mn - v : -v);
  }
}
__device__ __forceinline__ void sm_norm(uint32_t (&pk)[10], const float (&e)[20]) {
  float sp = ((e[0] + e[1]) + (e[2] + e[3])) + ((e[4] + e[5]) + (e[6] + e[7])) + (e[8] + e[9]);
  float sn = ((e[10] + e[11]) + (e[12] + e[13])) + ((e[14] + e[15]) + (e[16] + e[17])) + (e[18] + e[19]);
  sp += __shfl_xor_sync(0xffffffffu, sp, 1);
  sn += __shfl_xor_sync(0xffffffffu, sn, 1);
  const float rp = rcpf_(sp), rn = rcpf_(sn);
#pragma unroll
  for (int i = 0; i < 5; i++) { pk[i] = pack2(e[2 * i] * rp, e[2 * i + 1] * rp); pk[5 + i] = pack2(e[10 + 2 * i] * rn, e[11 + 2 * i] * rn); }
}
template <bool GUARD>
__device__ __forceinline__ void phi_step(const float (&pd)[20], float (&eB)[20], uint32_t (&pkA)[10], uint32_t (&pkB)[10], uint32_t fence_bar) {
  float eA[20];
  sm_exp<GUARD, 0>(eA, pd);
  sm_norm(pkB, eB);
  mbar_wait(fence_bar, 0);
  sm_exp<GUARD, 1>(eB, pd);
  sm_norm(pkA, eA);
}
constexpr uint32_t OFF_PHI = 4 * SLOT - 20480;
__device__ __forceinline__ void phi_store(const uint32_t (&pk)[10], uint32_t a) {
  stsm4(a, pk[0], pk[1], pk[2], pk[3]);
  stsm4(a + 8192, pk[4], pk[5], pk[6], pk[7]);
  stsm2(a + 16384, pk[8], pk[9]);
}
template <int U>
__device__ __forceinline__ void phi_swap(uint32_t (&R)[8][20], float (&pd)[20], const uint32_t (&pkA)[10], const uint32_t (&pkB)[10], bool keep) {
  if (keep) {
#pragma unroll
    for (int i = 0; i < 10; i++) { if (U < 7) R[U < 7 ? U + 1 : 7][2 * i + 1] = pkB[i]; R[U][2 * i] = pkA[i]; }
  }
#pragma unroll
  for (int i = 0; i < 20; i++) pd[i] = fmul_keep(__uint_as_float(R[U > 0 ? U - 1 : 0][i]));
}
template <int U>
__device__ __forceinline__ void o_issue(float (&od)[24], uint32_t (&R)[8][20], uint32_t sb) {
  WG_FENCE();
#pragma unroll
  for (int s = 0; s < 5; s++)
    wg_rs48(od, R[U][4 * s], R[U][4 * s + 1], R[U][4 * s + 2], R[U][4 * s + 3],
            mk_desc((sb & 0x3FFFF) >> 4, OFF_AUX + (U >> 1) * 7680 + s * 1536, 128, 256, 0), s > 0 ? 1 : 0);
  WG_COMMIT();
}
constexpr uint32_t OFF_OST = OFF_AUX + 30720;
__device__ __forceinline__ constexpr uint32_t ost_off(int t8) { return (t8 >> 2) < 4 ? OFF_OST + (t8 >> 2) * 8192 : OFF_AUX; }
template <int U>
__device__ __forceinline__ void o_finish(float (&od)[24], uint32_t oa, int c, int hi, int sw4, const float (&gq)[4]) {
  reg_fence(od);
  uint32_t pk[10];
#pragma unroll
  for (int hh = 0; hh < 2; hh++) {
    const float ra = gq[2 * (U & 1) + hh] * rcpf_(od[20 + 2 * hh] + 1e-6f), rb = gq[2 * (U & 1) + hh] * rcpf_(od[21 + 2 * hh] + 1e-6f);
    const float rm = c < 2 ? ra : rb;
#pragma unroll
    for (int j = 0; j < 5; j++) {
      const float rr = j < 2 ? ra : (j == 2 ? rm : rb);
      pk[2 * j + hh] = pack2(od[4 * j + 2 * hh] * rr, od[4 * j + 2 * hh + 1] * rr);
    }
  }
  constexpr int T0 = 5 * (U >> 1), ODD = T0 & 1, TS1 = ODD ? T0 : T0 + 4, TA = T0 + ODD;
  oa += (U & 1) * 4096;
  stsm2(oa + ost_off(TS1) + (((TS1 & 3) ^ sw4) << 4), pk[2 * (TS1 - T0)], pk[2 * (TS1 - T0) + 1]);
  stsm4(oa + ost_off(TA) + ((((TA & 3) + hi) ^ sw4) << 4), pk[2 * ODD], pk[2 * ODD + 1], pk[2 * ODD + 2], pk[2 * ODD + 3]);
  stsm4(oa + ost_off(TA + 2) + (((((TA + 2) & 3) + hi) ^ sw4) << 4), pk[2 * ODD + 4], pk[2 * ODD + 5], pk[2 * ODD + 6], pk[2 * ODD + 7]);
}

template <int SC>
__device__ __forceinline__ void h3_center(float (&acc)[2][96], const float (&nm)[4], const float2 (&cs)[4]) {
#pragma unroll
  for (int m = 0; m < 2; m++)
#pragma unroll
    for (int i = 0; i < 16; i++) acc[m][i] = fmaf(nm[2 * m + ((i >> 1) & 1)], (i & 1) ? cs[i >> 2].y : cs[i >> 2].x, acc[m][16 * SC + i]);
}

template <bool USE_SMID>
__global__ void __cluster_dims__(2, 1, 1) __launch_bounds__(384, 1) mega_kernel(const __grid_constant__ Params P) {
  extern __shared__ __align__(1024) uint8_t smem_raw[];
  const uint32_t sb = smem_u32(smem_raw);
  const uint32_t bars = sb + OFF_BAR;
  const int tid = threadIdx.x, lane = tid & 31;
  const int b = blockIdx.x;
  const uint32_t rank = b & 1, peer = rank ^ 1;
  int tpc = b >> 1;
  if (USE_SMID) {
    unsigned smid;
    asm volatile("mov.u32 %0, %%smid;" : "=r"(smid));
    tpc = smid >> 1;
  }
  const int q7 = ((tpc - 32) * 37) >> 8;
  const int g = tpc < 32 ? (tpc & 7) : tpc < 60 ? tpc - 31 - 7 * q7 : 0;
  const int pr = tpc < 32 ? (tpc >> 3) : tpc < 60 ? 4 + q7 : tpc - 58;
  const int spare = (tpc == 60 || tpc == 61) ? 2 * (tpc - 60) + (int)rank : -1;
  const bool mainc = spare < 0;
  const bool isX = mainc && pr < 4;
  const int jq = pr & 3;
  const int rb = 2 * g + rank;
  const int item = mainc ? g * 16 + pr * 2 + rank : 128 + spare;
  const int tt = (item * 205) >> 10, tf = item - 5 * tt;
  if (tid < 256) {
    sts128u(sb + (tid >> 6) * SLOT + 16384 + 10240 + (tid & 63) * 16, 0x3F803F80u, 0x3F803F80u, 0x3F803F80u, 0x3F803F80u);
    if (tid < 64) sts128u(sb + 4 * SLOT + 16384 + 10240 + tid * 16, 0x3F803F80u, 0x3F803F80u, 0x3F803F80u, 0x3F803F80u);
    fence_async_smem();
  } else if (lane == 0) {
    if (tid == 256) {
#pragma unroll
      for (int i = 0; i < 5; i++) mbar_init(bars + B_FULL + 8 * i, 1);
      if (spare < 2) {
#pragma unroll
        for (int s = 0; s < 2; s++) {
          mbar_expect_tx(bars + B_FULL + 8 * s, 26624);
          tma3d(sb + s * SLOT, &P.m[M_W1], bars + B_FULL + 8 * s, 0, s * 64, tf * 2);
          tma3d(sb + s * SLOT + 16384, &P.m[M_XT], bars + B_FULL + 8 * s, 0, tt * 80, s);
        }
      }
    } else if (tid == 288) {
      mbar_init(bars + B_KV, 1);
      if (mainc) {
        mbar_expect_tx(bars + B_KV, 21760);
        bulk_load(sb + OFF_PAD, P.x + (size_t)(tt * 80 + tf * 16) * DM, 20480, bars + B_KV);
        bulk_load(sb + OFF_PAD + 20480, P.gatew, 1280, bars + B_KV);
      }
    } else if (tid == 320) {
#pragma unroll
      for (int i = 5; i < 21; i++) mbar_init(bars + 8 * i, i < 10 ? 16 : (i == B_ST3 / 8) ? 32 : ((0x1C6800u >> i) & 1) ? 4 : 1);
    } else {
      sts128u(sb + OFF_ROLE, rb, isX, jq, spare);
#pragma unroll
      for (int i = 21; i < 30; i++) mbar_init(bars + 8 * i, (i < 24 || i >= 28) ? 4 : 1);
#pragma unroll
      for (int i = 0; i < 8; i++) mbar_init(bars + B_PHI + 8 * i, 4);
#pragma unroll
      for (int i = 0; i < 6; i++) mbar_init(bars + B_DEP2 + 8 * i, 1);
    }
    asm volatile("fence.mbarrier_init.release.cluster;" ::: "memory");
  }
  __syncthreads();
  asm volatile("barrier.cluster.arrive.relaxed.aligned;" ::: "memory");
  __syncwarp();
  asm volatile("barrier.cluster.wait.aligned;" ::: "memory");
  const int wg = __shfl_sync(0xffffffffu, tid >> 7, 0);
  const int w = __shfl_sync(0xffffffffu, (tid >> 5) & 3, 0);
  TS(44);

  if (spare >= 2) {
    if (spare == 2) {
#pragma unroll 1
      for (int i = tid; i < 32 * 24 * 40 / 4; i += 384) reinterpret_cast<float4*>(g_kv)[i] = make_float4(0.f, 0.f, 0.f, 0.f);
      reinterpret_cast<float4*>(g_cs3)[tid] = make_float4(0.f, 0.f, 0.f, 0.f);
      if (tid < 60) reinterpret_cast<uint4*>(g_hs + (tid < 40 ? 2 : 3) * DM + (tid < 20 ? 0 : 320))[tid % 20] = make_uint4(0, 0, 0, 0);
      fence_async_global();
      __syncthreads();
      if (tid == 0) flag_add_release(FZERO);
    }
    if (tid == 0) { flag_wait(FX1, 4); atomicAdd(&g_flag[FDONE * 32], 1u); }
    return;
  }

  if (wg == 2) {
    asm volatile("setmaxnreg.dec.sync.aligned.u32 32;");
    if (w < 1) {
      if (lane == 0) {
        const uint32_t bf = bars + B_FULL, be = bars + B_EMPTY;
        uint32_t par = 0x1C;
        int s = 2;
#pragma unroll 1
        for (int sg = 0; sg < (mainc ? 12 : 1); sg++) {
          if (!isX && sg == 4) continue;
          int n = 10, mA = M_XA, mB = M_WQKV, a1 = rb * 128, a2 = 0, as = 1, b2 = 5 * jq, dep = sg - 3;
          uint32_t offA = 0, offB = 16384 + rank * 10240, bytes = 36864;
          uint32_t nxt = sg <= 3 ? 0x00321 : 0x10324;
          bool mc = true;
          if (sg == 0) { n = 8; mA = M_XT; mB = M_W1; a1 = tt * 80; a2 = 2; b2 = tf * 2; offA = 16384; offB = 0; bytes = 26624; nxt = 0x04321; mc = false; }
          else if (sg <= 2) {
            if (isX) b2 += 20 * sg;
            else if (sg == 2) { mA = M_HSA; mB = M_W2; dep = 0; }
          } else if (sg == 3) { mA = M_X1A; mB = M_W3; b2 = 3 * pr; offB = 16384; bytes = 40960; mc = false; dep = 1; }
          else if (sg == 4) { n = 1; mA = M_X1ST; mB = M_X1ST; a2 = 5 * jq; offB = 20480; bytes = 40960; s = 4; mc = false; dep = -1; }
          else {
            if (sg == 5) s = 2;
            const int id = (G4ORD >> (4 * (sg - 5))) & 7;
            if (id == 7) { n = isX ? 5 + NXTRA : 5 - NXTRA; mA = M_OA; mB = M_WO; a2 = isX ? 0 : 5 + NXTRA; dep = 2; }
            else { n = 2; mA = M_H3A; mB = M_W4; as = 3; dep = (B_DEP2 - B_DEP) / 8 + id; a2 = (id < 3 ? id : id + 9) + (isX ? 0 : 6); }
          }
          const int b1 = sg == 4 ? a1 + 64 : a2 * 64 + (mc ? rank * 32 : 0), bs = as * 64;
          const CUtensorMap* pA = &P.m[mA];
          const CUtensorMap* pB = &P.m[mB];
          int ib = 0;
          if (dep >= 0) {
            int sa = s;
            const uint32_t t0 = clock32();
            const int npre = min(n, sg <= 3 ? 4 : 5);
#pragma unroll 1
            while (!mbar_test(bars + B_DEP + 8 * dep, 0) && clock32() - t0 < WAIT_CYCLES) {
              if (ib == npre) { mbar_wait(bars + B_DEP + 8 * dep, 0); break; }
              __nanosleep(32);
              if (mbar_test(be + 8 * s, (par >> s) & 1)) {
                mbar_expect_tx(bf + 8 * s, bytes);
                if (mc) tma3d_mc(sb + s * SLOT + offB, pB, bf + 8 * s, 0, b1 + ib * bs, b2, 3);
                else tma3d(sb + s * SLOT + offB, pB, bf + 8 * s, 0, b1 + ib * bs, b2);
                par ^= 1u << s;
                s = (nxt >> (4 * s)) & 7;
                ib++;
              }
            }
            fence_async_global();
#pragma unroll 1
            for (int ia = 0; ia < ib; ia++) {
              tma3d(sb + sa * SLOT + offA, pA, bf + 8 * sa, 0, a1, a2 + ia * as);
              sa = (nxt >> (4 * sa)) & 7;
            }
          }
#pragma unroll 1
          for (; ib < n; ib++) {
            mbar_wait(be + 8 * s, (par >> s) & 1);
            mbar_expect_tx(bf + 8 * s, bytes);
            tma3d(sb + s * SLOT + offA, pA, bf + 8 * s, 0, a1, a2 + ib * as);
            if (mc) tma3d_mc(sb + s * SLOT + offB, pB, bf + 8 * s, 0, b1 + ib * bs, b2, 3);
            else tma3d(sb + s * SLOT + offB, pB, bf + 8 * s, 0, b1 + ib * bs, b2);
            par ^= 1u << s;
            s = (nxt >> (4 * s)) & 7;
          }
          if (sg < 10) TSP(32 + sg);
        }
      }
    } else if (w < 2) {
      if (lane < NMAPS) prefetch_map(&P.m[lane]);
      __syncwarp();
      if (mainc) {
        if (!isX) {
          const int ta = max(0, rb * 128 - 2) / 80, tb = min(25, (rb * 128 + 129) / 80);
          if (lane <= tb - ta) flag_wait(FH + ta + lane, 5);
          if (lane == 3) flag_wait(FZERO, 1);
          __syncwarp();
          if (lane == 0) mbar_arrive(bars + B_DEP, 1);
          TSP(48);
        }
        if (lane == 0) { flag_wait(FX1 + rb, 4); mbar_arrive(bars + B_DEP + 8, 1); }
        TSP(49);
        __syncwarp();
        const unsigned* fp = &g_flag[(lane < 6 ? FH3 + rb * 6 + lane : lane == 6 ? FO + rb : FOZ) * 32];
        bool pend = lane < 8;
        int it = 0;
#pragma unroll 1
        while (__any_sync(0xffffffffu, pend) && ++it < SPIN_LIMIT) {
          if (pend && ld_flag(fp) >= (lane == 7 ? 128u : 4u)) {
            mbar_arrive(bars + (lane < 6 ? B_DEP2 + 8 * lane : B_DEP + 8 * (lane - 4)), 1);
            pend = false;
          }
        }
      }
    } else {
      if (w == 2) {
        const float tag = epoch_tag();
        float4 st[3];
        int it = 0;
        do {
#pragma unroll
          for (int i = 0; i < 3; i++) st[i] = ld_poll128(&g_xst[tt * 80 + min(lane + 32 * i, 79)]);
        } while (!__all_sync(0xffffffffu, tag_ok(st[0], tag) && tag_ok(st[1], tag) && tag_ok(st[2], tag)) && ++it < SPIN_LIMIT);
#pragma unroll
        for (int i = 0; i < 3; i++) {
          const int r = min(lane + 32 * i, 79);
          sts128f(sb + OFF_TOK + r * 16, st[i].x, GK1 * st[i].y, GK2 * st[i].y * st[i].y * st[i].y, 0.5f * st[i].y);
        }
        mbar_arrive(bars + B_ST3, 1);
        TSP(16);
        if (mainc) {
#pragma unroll 1
          for (int i = 0; i < 4; i += 2) {
            it = 0;
            do {
              st[0] = ld_poll128(&g_xst[rb * 128 + lane + 32 * i]);
              st[1] = ld_poll128(&g_xst[rb * 128 + lane + 32 * i + 32]);
            } while (!__all_sync(0xffffffffu, tag_ok(st[0], tag) && tag_ok(st[1], tag)) && ++it < SPIN_LIMIT);
            sts32f(sb + OFF_GATE + (lane + 32 * i) * 4, st[0].z);
            sts32f(sb + OFF_GATE + (lane + 32 * i + 32) * 4, st[1].z);
          }
          __syncwarp();
        }
        mbar_wait(bars + B_JOB0, 0);
        if (lane == 0) {
#pragma unroll 1
          for (int q = 0; q < 4; q++) {
            const int f0 = tf * 128 + q * 32, grp = f0 / 160;
            tma_st2d(&P.m[M_HSST], sb + (isX ? OFF_AUX : OFF_PAD) + q * 5120, f0, tt * 80 + 2 + (grp == 0 ? 1 : grp == 1 ? -1 : grp == 2 ? 2 : -2));
          }
          bulk_commit();
          bulk_wait0();
          flag_add(FH + tt);
          if (isX) {
            flag_wait(FZERO, 1);
            mbar_wait(bars + B_JOB1, 0);
            bulk_reduce(g_cs3 + jq * 384, sb + OFF_PAD, 1536);
            bulk_commit();
            bulk_wait0();
            flag_add(FCS3 + jq);
          }
          mbar_arrive(bars + B_SF1, 1);
        }
        __syncwarp();
        TSP(3);
        if (!mainc) {
          if (lane == 0) { flag_wait(FX1, 4); atomicAdd(&g_flag[FDONE * 32], 1u); }
        } else {
#pragma unroll
          for (int i = 0; i < 3; i++) sts128u(sb + OFF_TOK + min(lane + 32 * i, 79) * 16, 0u, 0u, 0u, 0u);
          fence_async_smem();
          __syncwarp();
          if (lane == 0) {
#pragma unroll 1
            for (int i = 0; i < 16; i++) {
              asm volatile("cp.async.bulk.global.shared::cta.bulk_group [%0], [%1], %2;" ::"l"(P.out + (item * 16 + i) * DM), "r"(sb + OFF_TOK), "r"(1280) : "memory");
              __nanosleep(200);
            }
            bulk_commit();
            bulk_wait0();
            flag_add(FOZ);
          }
          __syncwarp();
          if (lane == 0) flag_wait(FCS3 + (pr >> 1), 16);
          __syncwarp();
#pragma unroll
          for (int i = 0; i < 2; i++)
            if (lane + 32 * i < 48) { const float4 v = ld_poll128(&g_cs3[pr * 192 + (lane + 32 * i) * 4]); sts128f(sb + OFF_CS3 + (lane + 32 * i) * 16, v.x, v.y, v.z, v.w); }
          TSP(57);
          mbar_arrive(bars + B_ST3, 1);
          if (!isX) {
            if (lane == 0) {
              mbar_wait(bars + B_PHI + 16, 0);
              tma_st3d(&P.m[M_X1ST], sb + OFF_AUX, 0, rb * 128, 5 * jq);
              mbar_wait(bars + B_JOB0, 1);
              tma_st3d(&P.m[M_X1ST], sb + OFF_AUX + 20480, 0, rb * 128 + 64, 5 * jq);
              bulk_commit();
              bulk_wait0();
              flag_add(FX1 + rb);
            }
            __syncwarp();
            TSP(6);
            mbar_wait(bars + B_PHI + 24, 0);
            if (lane == 0) mbar_arrive(bars + B_AUXF, 1);
          }
          if (lane == 0) {
#pragma unroll 1
            for (int sc = 0; sc < 6; sc++) {
              mbar_wait(bars + B_RDY + 8 * sc, 0);
              tma_st2d(&P.m[M_H3ST], sb + SLOT + (sc == 5 ? 0 : sc) * 8192, pr * 192 + sc * 32, rb * 128);
              bulk_commit();
              if (sc & 1) {
                bulk_wait0();
                flag_add(FH3 + rb * 6 + (isX ? 0 : 3) + (sc >> 1));
                if (sc == 1) mbar_arrive(bars + B_WFREE, 1);
                TSP(10 + (sc >> 1));
              }
            }
            release_slot(bars + B_EMPTY + 8, true, peer, 16);
          }
        }
      } else if (mainc) {
        if (lane == 0) {
          const uint32_t t0 = clock32();
          l2_prefetch((const char*)P.w1 + item * 6400, 6400);
          while (clock32() - t0 < PF1_DELAY) __nanosleep(64);
          l2_prefetch((const char*)P.wqkv + item * 19200, 19200);
          while (clock32() - t0 < PF2_DELAY) __nanosleep(64);
          l2_prefetch((const char*)P.w2 + item * 6400, 6400);
          while (clock32() - t0 < PF3_DELAY) __nanosleep(64);
          l2_prefetch((const char*)P.w3 + item * 15360, 15360);
          while (clock32() - t0 < PF4_DELAY) __nanosleep(64);
          l2_prefetch((const char*)P.wo + item * 6400, 6400);
          l2_prefetch((const char*)P.w4 + item * 15360, 15360);
          flag_wait(FZERO, 1);
          if (isX) {
#pragma unroll 1
            for (int pp = 3; pp >= 0; pp--) {
              mbar_wait(bars + B_PHI + 32 + 8 * pp, 0);
              bulk_reduce(g_kv + jq * 7680 + pp * 1920, sb + OFF_PHI + pp * 20480, 7680);
              bulk_commit();
            }
            bulk_wait0();
            flag_add(FKV + jq);
            release_slot(bars + B_EMPTY + 8 * 3, true, peer, 16);
            release_slot(bars + B_EMPTY + 8 * 4, true, peer, 16);
          } else {
#pragma unroll 1
            for (int bx = 0; bx < 5; bx++) {
              if (bx == 0 || bx == 2) mbar_wait(bars + B_JOB1, bx >> 1);
              tma_st2d(&P.m[M_OST], sb + (bx < 4 ? OFF_OST + bx * 8192 : OFF_AUX), jq * 160 + bx * 32, rb * 128);
            }
            bulk_commit();
            bulk_wait0();
            flag_add(FO + rb);
            release_slot(bars + B_EMPTY + 8 * 4, true, peer, 16);
          }
        }
        __syncwarp();
        TSP(22);
        unsigned old = 0;
        if (lane == 0) {
          const uint32_t ost = sb + ((0x14032 >> (4 * ((isX ? 17 + NXTRA : 17 - NXTRA) % 5))) & 7) * SLOT;
          mbar_wait(bars + B_DEP + 24, 0);
#pragma unroll 1
          for (int m = 0; m < 2; m++) {
            mbar_wait(bars + B_FIN + 8 * m, 0);
            asm volatile("cp.reduce.async.bulk.tensor.3d.global.shared::cta.add.tile.bulk_group [%0, {%2, %3, %4}], [%1];" ::"l"(&P.m[M_OUT]),
                         "r"(ost + m * 20480), "r"(0), "r"(rb * 128 + 64 * m), "r"(5 * jq) : "memory");
          }
          bulk_commit();
          old = atomicAdd(&g_flag[FDONE * 32], 1u);
        }
        old = __shfl_sync(0xffffffffu, old, 0);
        if (old == gridDim.x - 1) {
#pragma unroll 1
          for (int i = lane; i < NFLAG; i += 32) g_flag[i * 32] = 0;
          if (lane == 0) g_epoch++;
        }
        if (lane == 0) bulk_wait0_read();
        TSP(28);
      }
    }
  } else if (wg == 0) {
    asm volatile("setmaxnreg.inc.sync.aligned.u32 232;");
    const bool elect = (tid == 0);
    const int c = lane & 3, r8 = lane >> 2, mi = lane >> 3, l8 = lane & 7;
    const int kr0 = tid / 5, jw = tid - 5 * kr0;
    uint2 wv[8];
#pragma unroll
    for (int i = 0; i < 8; i++) {
      const int rel = kr0 + 24 * (i & 1) - ((i >> 1) & 1) * 8;
      wv[i] = make_uint2(0, 0);
      if (rel >= 0 && rel < 40 && tid < 120)
        asm volatile("ld.global.nc.v2.u32 {%0, %1}, [%2];" : "=r"(wv[i].x), "=r"(wv[i].y) : "l"(P.wphi + ((jq * 8 + (i >> 1) * 2) * 20 + rel) * 20 + 4 * jw));
    }
    auto store_wphi = [&]() {
      if (tid < 120) {
#pragma unroll
        for (int i = 0; i < 8; i++) {
          const int kr = kr0 + 24 * (i & 1);
          const bool hb = kr - ((i >> 1) & 1) * 8 >= 20;
          sts128u(sb + OFF_W + ((i >> 1) * 3 + (kr >> 4)) * 1280 + jw * 256 + (kr & 15) * 16, hb ? 0u : wv[i].x, hb ? 0u : wv[i].y, hb ? wv[i].x : 0u,
                  hb ? wv[i].y : 0u);
        }
      }
    };
    {
      float acc[2][44];
#pragma unroll 1
      for (int i = 0; i < 10; i++) {
        const int s = i >= 5 ? i - 5 : i;
        const uint32_t sw = ((sb & 0x3FFFF) + s * SLOT) >> 4;
        mbar_wait(bars + B_FULL + 8 * s, i >= 5);
        if (i == 0) TS(1);
        WG_FENCE();
#pragma unroll
        for (int k = 0; k < 4; k++)
#pragma unroll
          for (int m = 0; m < 2; m++) wg_t88(acc[m], mk_desc(sw, m * 8192 + k * 2048, 8192, 1024, 1), mk_desc(sw, 16384 + k * 32, 16, 1024, 1), (k > 0 || i > 0) ? 1 : 0);
        WG_COMMIT();
        if (i == 9) bar_arrive(NB_ORD1, 256);
        WG_WAIT(1);
        if (i > 0 && elect) release_slot(bars + B_EMPTY + 8 * (s == 0 ? 4 : s - 1), mainc, peer, 16);
      }
      WG_WAIT(0);
      reg_fence(acc[0]);
      reg_fence(acc[1]);
      TS(2);
      if (elect) {
        if (mainc && !isX) {
          mbar_expect_tx(bars + B_XRES, 40960);
          tma3d(sb + OFF_AUX, &P.m[M_XR], bars + B_XRES, 0, rb * 128, 5 * jq);
          tma3d(sb + OFF_AUX + 20480, &P.m[M_XR], bars + B_XRES, 0, rb * 128 + 64, 5 * jq);
        }
      }
      mbar_wait(bars + B_ST3, 0);
      bar_sync(NB_WG0, 128);
      const int tok0 = 8 * (mi >> 1) + l8;
      const uint32_t hst = sb + (isX ? OFF_AUX : OFF_PAD) + (w >> 1) * 5120 + tok0 * 64 + ((((w & 1) * 2 + (mi & 1)) ^ ((tok0 >> 1) & 3)) << 4);
      float4 st[20];
#pragma unroll
      for (int e = 0; e < 20; e++) st[e] = lds128f(sb + OFF_TOK + (8 * (e >> 1) + 2 * c + (e & 1)) * 16);
#pragma unroll 1
      for (int m = 0; m < 2; m++) {
#pragma unroll
        for (int jp = 0; jp < 5; jp++) {
          float t[8];
#pragma unroll
          for (int i = 0; i < 8; i++) {
            const float4 s4 = st[4 * jp + 2 * (i >> 2) + (i & 1)];
            t[i] = gelu_s(fmaf(-s4.x, acc[0][40 + (i & 2)], acc[0][8 * jp + i]), s4.y, s4.z, s4.w);
          }
          stsm4t(hst + m * 10240 + jp * 1024, pack2(t[0], t[1]), pack2(t[2], t[3]), pack2(t[4], t[5]), pack2(t[6], t[7]));
        }
#pragma unroll
        for (int i = 0; i < 44; i++) acc[0][i] = acc[1][i];
      }
      signal_tile(bars + B_JOB0, lane);
      TS(14);
    }
    if (mainc) {
      const int row0 = 16 * w + 8 * (mi & 1) + l8;
      {
        float acc[2][80];
        const uint32_t xst = sb + OFF_AUX + row0 * 64;
        const int sw4 = (row0 >> 1) & 3;
        if (!isX) {
          mbar_wait(bars + B_XRES, 0);
#pragma unroll
          for (int m = 0; m < 2; m++)
#pragma unroll
            for (int jp = 0; jp < 10; jp++) {
              uint32_t r0, r1, r2, r3;
              ldsm4(xst + m * 20480 + (jp >> 1) * 4096 + (((2 * (jp & 1) + (mi >> 1)) ^ sw4) << 4), r0, r1, r2, r3);
              acc[m][8 * jp + 0] = bf_lo(r0); acc[m][8 * jp + 1] = bf_hi(r0);
              acc[m][8 * jp + 2] = bf_lo(r1); acc[m][8 * jp + 3] = bf_hi(r1);
              acc[m][8 * jp + 4] = bf_lo(r2); acc[m][8 * jp + 5] = bf_hi(r2);
              acc[m][8 * jp + 6] = bf_lo(r3); acc[m][8 * jp + 7] = bf_hi(r3);
            }
          reg_fence(acc[0]);
          reg_fence(acc[1]);
        }
        if (!isX) mbar_wait(bars + B_SF1, 0);
        store_wphi();
        signal_tile(bars + B_WPHI, lane);
      if (isX) {
        const int cg = w * 12 + min(lane & 15, 11);
        const uint4* src = reinterpret_cast<const uint4*>(P.w3 + (size_t)(rb * 40 + (lane >> 4) * 20) * FF + jq * 384) + cg;
        float cs[8];
#pragma unroll
        for (int i = 0; i < 8; i++) cs[i] = 0.f;
#pragma unroll 1
        for (int h = 0; h < 20; h += 10) {
          uint4 cv[10];
#pragma unroll
          for (int q = 0; q < 10; q++) cv[q] = __ldg(src + (h + q) * (FF / 8));
#pragma unroll
          for (int q = 0; q < 10; q++) {
            cs[0] += bf_lo(cv[q].x); cs[1] += bf_hi(cv[q].x); cs[2] += bf_lo(cv[q].y); cs[3] += bf_hi(cv[q].y);
            cs[4] += bf_lo(cv[q].z); cs[5] += bf_hi(cv[q].z); cs[6] += bf_lo(cv[q].w); cs[7] += bf_hi(cv[q].w);
          }
        }
#pragma unroll
        for (int i = 0; i < 8; i++) cs[i] += __shfl_xor_sync(0xffffffffu, cs[i], 16);
        sts128f(sb + OFF_PAD + cg * 32, cs[0], cs[1], cs[2], cs[3]);
        sts128f(sb + OFF_PAD + cg * 32 + 16, cs[4], cs[5], cs[6], cs[7]);
        signal_tile(bars + B_JOB1, lane);
        TS(60);
      }
        bar_sync(NB_ORD0, 256);
        TS(4);
        auto stage = [&](int m) {
#pragma unroll
          for (int jp = 0; jp < 10; jp++) {
            const int t8 = 2 * jp + (mi >> 1);
            const uint32_t ax = sb + 2 * SLOT + (t8 + (t8 >= 5) + (t8 >= 15)) * 2048 + row0 * 16 + m * 1024;
            const uint32_t ay = xst + m * 20480 + (jp >> 1) * 4096 + (((2 * (jp & 1) + (mi >> 1)) ^ sw4) << 4);
            stsm4(isX ? ax : ay, pack2(acc[m][8 * jp], acc[m][8 * jp + 1]), pack2(acc[m][8 * jp + 2], acc[m][8 * jp + 3]),
                  pack2(acc[m][8 * jp + 4], acc[m][8 * jp + 5]), pack2(acc[m][8 * jp + 6], acc[m][8 * jp + 7]));
          }
        };
        main_n160<true>(acc, sb, 10, 2, 0x3, 0x0321, isX, isX ? 2 : 0, peer, elect, [&](int m) {
          if (m == 0) {
            if (!isX) { stage(0); signal_tile(bars + B_PHI + 16, lane); }
          } else {
            TS(5);
            if (isX) {
              bar_arrive(NB_VM, 256);
              bar_sync(NB_WG0, 128);
              sts128u(sb + 2 * SLOT + 5 * 2048 + tid * 16, 0x3F803F80u, 0x3F803F80u, 0x3F803F80u, 0x3F803F80u);
              sts128u(sb + 2 * SLOT + 16 * 2048 + tid * 16, 0x3F803F80u, 0x3F803F80u, 0x3F803F80u, 0x3F803F80u);
              stage(0);
            }
            stage(1);
          }
        } TSARG(84));
        if (isX) {
          fence_async_smem();
          bar_sync(NB_WG0, 128);
          TS(21);
#pragma unroll 1
          for (int pp = 3; pp >= 0; pp--) {
            mbar_wait(bars + B_PHI + 8 * pp, 0);
            float dk[40];
            const uint32_t va = ((sb & 0x3FFFF) + 2 * SLOT + ((pp >> 1) * 11 + (pp & 1) * 5) * 2048) >> 4, pa = ((sb & 0x3FFFF) + OFF_PHI + pp * 20480) >> 4;
            WG_FENCE();
#pragma unroll
            for (int ks = 0; ks < 8; ks++) wg_tt80(dk, mk_desc(va, ks * 256, 128, 2048, 0), mk_desc(pa, ks * 256, 128, 2048, 0), ks > 0 ? 1 : 0);
            WG_COMMIT();
            WG_WAIT(0);
            reg_fence(dk);
            bar_sync(NB_WG0, 128);
#pragma unroll
            for (int hh = 0; hh < 2; hh++) {
              const int row = 16 * w + 8 * hh + r8 - 8 * (pp & 1);
              const int zr = row - ((pp & 1) ? -8 : 40), hb = c >> 1;
              const bool isz = zr >= 0 && zr < 4;
              const int d = isz ? 20 + zr : row - 20 * hb;
              if (isz || (d >= 0 && d < 20)) {
                const uint32_t dst = sb + OFF_PHI + pp * 20480 + (hb * 240 + d) * 16 + 8 * (c & 1);
#pragma unroll
                for (int j = 0; j < 10; j++) sts64f(dst + 384 * j, dk[4 * j + 2 * hh], dk[4 * j + 2 * hh + 1]);
              }
            }
            signal_tile(bars + B_PHI + 32 + 8 * pp, lane);
          }
          if (elect) release_slot(bars + B_EMPTY + 8 * 2, true, peer, 16);
        } else {
          signal_tile(bars + B_JOB0, lane);
          TS(15);
        }
      }
      float acc[2][96];
      TS(7);
#pragma unroll 1
      for (int kb = 0; kb < 10; kb++) {
        const int i = 20 + kb;
        const uint32_t sa = ((sb & 0x3FFFF) + (i & 3) * SLOT) >> 4;
        TS(64 + 2 * i);
        mbar_wait(bars + B_FULL + 8 * (i & 3), (i >> 2) & 1);
        TS(65 + 2 * i);
        if (kb == 0) TS(8);
        WG_FENCE();
#pragma unroll
        for (int k = 0; k < 4; k++) {
          const uint64_t db = mk_desc(sa, 16384 + k * 2048, 8192, 1024, 1);
#pragma unroll
          for (int m = 0; m < 2; m++) wg_n192(acc[m], mk_desc(sa, m * 8192 + k * 32, 16, 1024, 1), db, (k > 0 || kb > 0) ? 1 : 0);
        }
        WG_COMMIT();
        if (kb == 9) bar_arrive(NB_ORD1, 256);
        WG_WAIT(1);
        if (kb > 0 && elect) release_slot(bars + B_EMPTY + 8 * ((i - 1) & 3), true, peer, 16);
      }
      WG_WAIT(0);
      reg_fence(acc[0]);
      reg_fence(acc[1]);
      TS(9);
      bar_sync(NB_STAT, 256);
      float nm[4], c1[4], c2[4], hr[4];
#pragma unroll
      for (int q = 0; q < 4; q++) {
        const float2 v = lds64f(sb + OFF_TOK + (64 * (q >> 1) + 16 * w + 8 * (q & 1) + r8) * 8);
        nm[q] = -v.x; c1[q] = GK1 * v.y; c2[q] = GK2 * v.y * v.y * v.y;
        hr[q] = 0.5f * v.y * (1.f - lds32f(sb + OFF_GATE + (64 * (q >> 1) + 16 * w + 8 * (q & 1) + r8) * 4));
      }
      TS(29);
      const uint32_t h3a = sb + SLOT + row0 * 64;
      const int sw4 = (row0 >> 1) & 3;
      int bu = 0;
      float2 cs[4];
#pragma unroll
      for (int e = 0; e < 4; e++) cs[e] = lds64f(sb + OFF_CS3 + (8 * e + 2 * c) * 4);
      h3_center<0>(acc, nm, cs);
#pragma unroll 1
      for (int sc = 1;; sc++) {
        uint32_t pk[16];
#pragma unroll
        for (int m = 0; m < 2; m++)
#pragma unroll
          for (int i = 0; i < 8; i++) {
            const int q = 2 * m + (i & 1);
            pk[8 * m + i] = pack2(gelu_s(acc[m][2 * i], c1[q], c2[q], hr[q]), gelu_s(acc[m][2 * i + 1], c1[q], c2[q], hr[q]));
          }
#pragma unroll
        for (int e = 0; e < 4; e++) cs[e] = lds64f(sb + OFF_CS3 + (32 * sc + 8 * e + 2 * c) * 4);
#pragma unroll
        for (int m = 0; m < 2; m++)
#pragma unroll
          for (int u = 0; u < 2; u++)
            stsm4(h3a + bu * 8192 + m * 4096 + (((2 * u + (mi >> 1)) ^ sw4) << 4), pk[8 * m + 4 * u], pk[8 * m + 4 * u + 1], pk[8 * m + 4 * u + 2], pk[8 * m + 4 * u + 3]);
        signal_tile(bars + B_RDY + 8 * (sc - 1), lane);
        TS(169 + sc);
        if (sc == 6) break;
        if (sc & 4) { if (sc & 1) h3_center<5>(acc, nm, cs); else h3_center<4>(acc, nm, cs); }
        else if (sc & 2) { if (sc & 1) h3_center<3>(acc, nm, cs); else h3_center<2>(acc, nm, cs); }
        else h3_center<1>(acc, nm, cs);
        bu = sc == 5 ? 0 : sc;
        if (sc == 5) mbar_wait(bars + B_WFREE, 0);
      }
      TS(13);
    }
  } else {
    asm volatile("setmaxnreg.inc.sync.aligned.u32 240;");
    const int t = tid - 128;
    const bool elect = (t == 0);
    {
      const int ch = t & 7, tok = tt * 80 + tf * 16 + (t >> 3);
      const float tag = epoch_tag();
      float s1 = 0.f, s2 = 0.f, sg = 0.f;
      if (mainc) {
        mbar_wait(bars + B_KV, 0);
        const uint32_t xa = sb + OFF_PAD + (t >> 3) * 1280 + ch * 16, ga = sb + OFF_PAD + 20480 + ch * 16;
#pragma unroll 2
        for (int i = 0; i < 10; i++) {
          const uint4 v = lds128u(xa + i * 128), gv = lds128u(ga + i * 128);
          const uint32_t xv[4] = {v.x, v.y, v.z, v.w}, gw[4] = {gv.x, gv.y, gv.z, gv.w};
#pragma unroll
          for (int q = 0; q < 4; q++) {
            const float a0 = bf_lo(xv[q]), a1 = bf_hi(xv[q]);
            s1 += a0 + a1;
            s2 = fmaf(a0, a0, fmaf(a1, a1, s2));
            sg = fmaf(a0, bf_lo(gw[q]), fmaf(a1, bf_hi(gw[q]), sg));
          }
        }
      }
#pragma unroll
      for (int o = 1; o < 8; o <<= 1) {
        s1 += __shfl_xor_sync(0xffffffffu, s1, o);
        s2 += __shfl_xor_sync(0xffffffffu, s2, o);
        sg += __shfl_xor_sync(0xffffffffu, sg, o);
      }
      if (ch == 0) {
        const float mean = s1 * (1.f / DM);
        g_xst[tok] = make_float4(mean, rsqrtf(fmaxf(s2 * (1.f / DM) - mean * mean, 0.f) + 1e-5f), rcpf_(1.f + ex2f(-sg * LOG2E)), tag);
      }
      bar_sync(NB_ORD1, 256);
      TS(17);
    }
    if (mainc) {
      uint32_t R[8][20];
      float pd[20];
      {
        float acc[2][80];
        main_n160<false>(acc, sb, 10, 0, 0x0, 0x0321, true, 0, peer, elect, [](int) {} TSARG(64));
        TS(19);
        uint32_t af[40];
        float pl[7][20];
#pragma unroll
        for (int i = 0; i < 40; i++) af[i] = pack2(acc[0][2 * i], acc[0][2 * i + 1]);
        mbar_wait(bars + B_WPHI, 0);
        p_issue(pl[0], pl[2], pl[4], pl[6], af, sb, -1);
        mbar_wait(bars + B_WPHI, 0);
        reg_fence(acc[1]);
#pragma unroll
        for (int i = 0; i < 40; i++) af[i] = pack2(acc[1][2 * i], acc[1][2 * i + 1]);
        p_issue(pl[1], pl[3], pl[5], pd, af, sb, NB_ORD0);
#pragma unroll
        for (int u = 0; u < 7; u++)
#pragma unroll
          for (int i = 0; i < 20; i++) R[u][i] = __float_as_uint(pl[u][i]);
      }
      TS(18);
      {
        bar_sync(NB_WG1, 128);
        mbar_wait(bars + B_SF1, 0);
        uint32_t pa = sb + OFF_PHI + ((t >> 3) & 3) * 2048 + ((t >> 5) * 16 + (t & 7)) * 16;
        asm volatile("" : "+r"(pa));
#pragma unroll
        for (int i = 0; i < 20; i++) pd[i] *= LOG2E;
        float eB[20];
#pragma unroll
        for (int i = 0; i < 20; i++) eB[i] = 1.f;
        uint32_t pkA[10], pkB[10];
#pragma unroll 1
        for (int u = 7; u >= 0; u--) {
          float am = fmaxf(fabsf(pd[0]), fabsf(pd[1]));
#pragma unroll
          for (int i = 2; i < 20; i += 2) am = fmaxf(am, fmaxf(fabsf(pd[i]), fabsf(pd[i + 1])));
          if (__all_sync(0xffffffffu, am < 120.f)) phi_step<false>(pd, eB, pkA, pkB, bars + B_WPHI);
          else phi_step<true>(pd, eB, pkA, pkB, bars + B_WPHI);
          if (isX) {
            if (u < 7) phi_store(pkB, pa + ((u + 1) >> 1) * 20480 + ((u + 1) & 1) * 1024 + 128);
            if ((u & 1) && u < 7) signal_tile(bars + B_PHI + 4 * (u + 1), lane);
            if (u == 1) bar_sync(NB_VM, 256);
            phi_store(pkA, pa + (u >> 1) * 20480 + (u & 1) * 1024);
          }
          if (u & 4) {
            if (u & 2) { if (u & 1) phi_swap<7>(R, pd, pkA, pkB, !isX); else phi_swap<6>(R, pd, pkA, pkB, !isX); }
            else { if (u & 1) phi_swap<5>(R, pd, pkA, pkB, !isX); else phi_swap<4>(R, pd, pkA, pkB, !isX); }
          } else {
            if (u & 2) { if (u & 1) phi_swap<3>(R, pd, pkA, pkB, !isX); else phi_swap<2>(R, pd, pkA, pkB, !isX); }
            else { if (u & 1) phi_swap<1>(R, pd, pkA, pkB, !isX); else phi_swap<0>(R, pd, pkA, pkB, !isX); }
          }
          TS(180 + u);
        }
        sm_norm(pkB, eB);
#pragma unroll
        for (int i = 0; i < 10; i++) R[0][2 * i + 1] = pkB[i];
        if (isX) { phi_store(pkB, pa + 128); signal_tile(bars + B_PHI, lane); }
      }
      TS(20);
      const int t = fresh_tid() - 128, lane = t & 31, w = t >> 5, c = lane & 3, r8 = lane >> 2, mi = lane >> 3;
      const bool elect = t == 0;
      const int jq = lds128u(sb + OFF_ROLE).z;
      const int row0 = 16 * w + 8 * (mi & 1) + (lane & 7);
      float gq[4];
#pragma unroll
      for (int q = 0; q < 4; q++) gq[q] = lds32f(sb + OFF_GATE + (64 * (q >> 1) + 16 * w + 8 * (q & 1) + r8) * 4);
      const int rb = lds128u(sb + OFF_ROLE).x;
      const float tag = epoch_tag();
      if (!isX) {
        mbar_wait(bars + B_JOB0, 1);
        float s = 0.f, q = 0.f;
#pragma unroll 2
        for (int i = 0; i < 20; i++) {
          const uint4 v = lds128u(sb + OFF_AUX + (t >> 6) * 20480 + (i >> 2) * 4096 + (t & 63) * 64 + (((i & 3) ^ ((t >> 1) & 3)) << 4));
          const float a0 = bf_lo(v.x), a1 = bf_hi(v.x), a2 = bf_lo(v.y), a3 = bf_hi(v.y), a4 = bf_lo(v.z), a5 = bf_hi(v.z), a6 = bf_lo(v.w), a7 = bf_hi(v.w);
          s += ((a0 + a1) + (a2 + a3)) + ((a4 + a5) + (a6 + a7));
          q += fmaf(a0, a0, fmaf(a1, a1, fmaf(a2, a2, a3 * a3))) + fmaf(a4, a4, fmaf(a5, a5, fmaf(a6, a6, a7 * a7)));
        }
        g_st1[jq * SEQ + rb * 128 + t] = make_float4(s, q, 0.f, tag);
        __syncwarp();
        if (lane == 0) mbar_arrive(bars + B_PHI + 24, 1);
        TS(60);
      }
      {
        float4 st[4];
        int it = 0;
        do {
#pragma unroll
          for (int j = 0; j < 4; j++) st[j] = ld_poll128(&g_st1[j * SEQ + rb * 128 + t]);
        } while (!(tag_ok(st[0], tag) && tag_ok(st[1], tag) && tag_ok(st[2], tag) && tag_ok(st[3], tag)) && ++it < SPIN_LIMIT);
        const float mean = (st[0].x + st[1].x + st[2].x + st[3].x) * (1.f / DM);
        mbar_wait(bars + B_ST3, 1);
        sts64f(sb + OFF_TOK + t * 8, mean, rsqrtf(fmaxf((st[0].y + st[1].y + st[2].y + st[3].y) * (1.f / DM) - mean * mean, 0.f) + 1e-5f));
        bar_arrive(NB_STAT, 256);
        TS(58);
      }
      if (!isX) {
        mbar_wait(bars + B_AUXF, 0);
        uint32_t ad[4];
#pragma unroll
        for (int i = 0; i < 4; i++) {
          const int e = min(t, 119) + 120 * (i & 1), j = e / 24, d = e - 24 * j, hb = i >> 1;
          const int n = d < 20 ? d + 20 * hb : hb + 2 * d;
          ad[i] = sb + OFF_AUX + (j >> 1) * 1536 + (n >> 3) * 256 + (j & 1) * 128 + (n & 7) * 16 + hb * 8;
        }
#pragma unroll
        for (int i = 0; i < 16; i++) sts64u((ad[i & 3] ^ 8) + (i >> 2) * 7680, 0u, 0u);
        const uint32_t ra = sb + OFF_AUX + 30720 + min(t, 119) * 16;
        if (elect) {
          flag_wait(FKV + jq, 16);
          TS(59);
          mbar_expect_tx(bars + B_KV, 30720);
          bulk_load(sb + OFF_AUX + 30720, g_kv + jq * 7680, 30720, bars + B_KV);
        }
        mbar_wait(bars + B_KV, 1);
        TS(21);
#pragma unroll
        for (int p2 = 0; p2 < 2; p2++) {
          float4 v[8];
#pragma unroll
          for (int i = 0; i < 8; i++) v[i] = lds128f(ra + (8 * p2 + i) * 1920);
#pragma unroll
          for (int i = 0; i < 8; i++) sts64u(ad[i & 3] + (2 * p2 + (i >> 2)) * 7680, pack2(v[i].x, v[i].y), pack2(v[i].z, v[i].w));
        }
        fence_async_smem();
        bar_sync(NB_WG1, 128);
        TS(30);
        {
          const uint32_t oa = sb + row0 * 64;
          const int hi = mi >> 1, sw4 = (row0 >> 1) & 3;
          float oA[24], oB[24];
          o_issue<0>(oA, R, sb);
          o_issue<1>(oB, R, sb);
          WG_WAIT(1); o_finish<0>(oA, oa, c, hi, sw4, gq); o_issue<2>(oA, R, sb);
          WG_WAIT(1); o_finish<1>(oB, oa, c, hi, sw4, gq); o_issue<3>(oB, R, sb);
          WG_WAIT(1); o_finish<2>(oA, oa, c, hi, sw4, gq); o_issue<4>(oA, R, sb);
          WG_WAIT(1); o_finish<3>(oB, oa, c, hi, sw4, gq); o_issue<5>(oB, R, sb);
          signal_tile(bars + B_JOB1, lane);
          WG_WAIT(1); o_finish<4>(oA, oa, c, hi, sw4, gq); o_issue<6>(oA, R, sb);
          WG_WAIT(1); o_finish<5>(oB, oa, c, hi, sw4, gq); o_issue<7>(oB, R, sb);
          bar_sync(NB_WG1, 128);
          WG_WAIT(1); o_finish<6>(oA, oa, c, hi, sw4, gq);
          WG_WAIT(0); o_finish<7>(oB, oa, c, hi, sw4, gq);
          signal_tile(bars + B_JOB1, lane);
        }
        TS(31);
      }
      const uint4 role = lds128u(sb + OFF_ROLE);
      const bool isX = role.y;
      const uint32_t peer = (blockIdx.x & 1) ^ 1;
      const uint32_t xst = sb + OFF_AUX + row0 * 64;
      const uint32_t ost = sb + ((0x14032 >> (4 * ((isX ? 17 + NXTRA : 17 - NXTRA) % 5))) & 7) * SLOT;
      const int sw4 = (row0 >> 1) & 3;
      float acc[2][80];
      if (isX) {
        mbar_wait(bars + B_FULL + 8 * 4, 0);
#pragma unroll 1
        for (int m = 0; m < 2; m++) {
          const float ga = 1.f - (m ? gq[2] : gq[0]), gb = 1.f - (m ? gq[3] : gq[1]);
#pragma unroll
          for (int i = 0; i < 80; i++) acc[0][i] = acc[1][i];
#pragma unroll
          for (int jp = 0; jp < 10; jp++) {
            uint32_t r0, r1, r2, r3;
            ldsm4(xst + m * 20480 + (jp >> 1) * 4096 + (((2 * (jp & 1) + (mi >> 1)) ^ sw4) << 4), r0, r1, r2, r3);
            acc[1][8 * jp + 0] = ga * bf_lo(r0); acc[1][8 * jp + 1] = ga * bf_hi(r0);
            acc[1][8 * jp + 2] = gb * bf_lo(r1); acc[1][8 * jp + 3] = gb * bf_hi(r1);
            acc[1][8 * jp + 4] = ga * bf_lo(r2); acc[1][8 * jp + 5] = ga * bf_hi(r2);
            acc[1][8 * jp + 6] = gb * bf_lo(r3); acc[1][8 * jp + 7] = gb * bf_hi(r3);
          }
        }
        __syncwarp();
        if (lane == 0) release_slot(bars + B_EMPTY + 8 * 4, true, peer, 4);
      }
      bar_sync(NB_ORD1, 256);
      TS(23);
      main_n160<true>(acc, sb, isX ? 17 + NXTRA : 17 - NXTRA, 2, isX ? 0x1Cu : 0x0Cu, 0x10324, !isX, 5, peer, elect, [&](int m) {
        if (m) TS(27);
#pragma unroll
        for (int jp = 0; jp < 10; jp++)
          stsm4(ost + row0 * 64 + m * 20480 + (jp >> 1) * 4096 + (((2 * (jp & 1) + (mi >> 1)) ^ sw4) << 4), pack2(acc[m][8 * jp], acc[m][8 * jp + 1]),
                pack2(acc[m][8 * jp + 2], acc[m][8 * jp + 3]), pack2(acc[m][8 * jp + 4], acc[m][8 * jp + 5]), pack2(acc[m][8 * jp + 6], acc[m][8 * jp + 7]));
        signal_tile(bars + B_FIN + 8 * m, lane);
      } TSARG(124));
    }
  }
}

typedef CUresult (*EncFn)(CUtensorMap*, CUtensorMapDataType, cuuint32_t, void*, const cuuint64_t*, const cuuint64_t*, const cuuint32_t*,
                          const cuuint32_t*, CUtensorMapInterleave, CUtensorMapSwizzle, CUtensorMapL2promotion, CUtensorMapFloatOOBfill);

static void map2d(EncFn enc, CUtensorMap* m, const void* p, int rows, int cols, int bc, int br) {
  cuuint64_t dim[2] = {(cuuint64_t)cols, (cuuint64_t)rows};
  cuuint64_t str[1] = {(cuuint64_t)cols * 2};
  cuuint32_t box[2] = {(cuuint32_t)bc, (cuuint32_t)br};
  cuuint32_t es[2] = {1, 1};
  enc(m, CU_TENSOR_MAP_DATA_TYPE_BFLOAT16, 2, (void*)p, dim, str, box, es, CU_TENSOR_MAP_INTERLEAVE_NONE,
      bc == 64 ? CU_TENSOR_MAP_SWIZZLE_128B : CU_TENSOR_MAP_SWIZZLE_64B, CU_TENSOR_MAP_L2_PROMOTION_L2_128B, CU_TENSOR_MAP_FLOAT_OOB_FILL_NONE);
}
static void map3d(EncFn enc, CUtensorMap* m, const void* p, int rows, int cols, int bc, int br, int na) {
  cuuint64_t dim[3] = {(cuuint64_t)bc, (cuuint64_t)rows, (cuuint64_t)(cols / bc)};
  cuuint64_t str[2] = {(cuuint64_t)cols * 2, (cuuint64_t)bc * 2};
  cuuint32_t box[3] = {(cuuint32_t)bc, (cuuint32_t)br, (cuuint32_t)na};
  cuuint32_t es[3] = {1, 1, 1};
  enc(m, CU_TENSOR_MAP_DATA_TYPE_BFLOAT16, 3, (void*)p, dim, str, box, es, CU_TENSOR_MAP_INTERLEAVE_NONE,
      bc == 64 ? CU_TENSOR_MAP_SWIZZLE_128B : CU_TENSOR_MAP_SWIZZLE_64B, CU_TENSOR_MAP_L2_PROMOTION_L2_128B, CU_TENSOR_MAP_FLOAT_OOB_FILL_NONE);
}

extern "C" void kernel_launch(void* const* d_in, const int* in_sizes, int n_in, void* d_out, int out_size) {
  (void)in_sizes; (void)n_in; (void)out_size;
  EncFn enc = nullptr;
  cudaDriverEntryPointQueryResult qr;
  cudaGetDriverEntryPoint("cuTensorMapEncodeTiled", (void**)&enc, cudaEnableDefault, &qr);
  Params P;
  P.x = (const bf16*)d_in[0]; P.wqkv = (const bf16*)d_in[1]; P.wphi = (const bf16*)d_in[2]; P.wo = (const bf16*)d_in[3];
  P.w1 = (const bf16*)d_in[5]; P.w2 = (const bf16*)d_in[6]; P.w3 = (const bf16*)d_in[7]; P.w4 = (const bf16*)d_in[8];
  P.gatew = (const bf16*)d_in[9];
  P.out = (bf16*)d_out;
  void *hs, *x1, *o, *h3;
  cudaGetSymbolAddress(&hs, g_hs); cudaGetSymbolAddress(&x1, g_x1); cudaGetSymbolAddress(&o, g_o); cudaGetSymbolAddress(&h3, g_h3);
  map3d(enc, &P.m[M_XA], P.x, SEQ, DM, 64, 128, 1);
  map3d(enc, &P.m[M_XT], P.x, SEQ, DM, 64, 80, 1);
  map3d(enc, &P.m[M_XR], P.x, SEQ, DM, 32, 64, 5);
  map3d(enc, &P.m[M_W1], P.w1, DM, DM, 64, 64, 2);
  map3d(enc, &P.m[M_WQKV], P.wqkv, DM, 3 * DM, 32, 32, 5);
  map3d(enc, &P.m[M_W2], P.w2, DM, DM, 32, 32, 5);
  map3d(enc, &P.m[M_W3], P.w3, DM, FF, 64, 64, 3);
  map3d(enc, &P.m[M_WO], P.wo, DM, DM, 32, 32, 5);
  map3d(enc, &P.m[M_W4], P.w4, FF, DM, 32, 32, 5);
  map2d(enc, &P.m[M_HSST], hs, SEQ + 2, DM, 32, 80);
  map3d(enc, &P.m[M_HSA], (const bf16*)hs + 2 * DM, SEQ, DM, 64, 128, 1);
  map3d(enc, &P.m[M_X1ST], x1, SEQ, DM, 32, 64, 5);
  map3d(enc, &P.m[M_X1A], x1, SEQ, DM, 64, 128, 1);
  map2d(enc, &P.m[M_H3ST], h3, SEQ, FF, 32, 128);
  map3d(enc, &P.m[M_H3A], h3, SEQ, FF, 64, 128, 1);
  map2d(enc, &P.m[M_OST], o, SEQ, DM, 32, 128);
  map3d(enc, &P.m[M_OA], o, SEQ, DM, 64, 128, 1);
  map3d(enc, &P.m[M_OUT], d_out, SEQ, DM, 32, 64, 5);
  int nsm = 0;
  cudaDeviceGetAttribute(&nsm, cudaDevAttrMultiProcessorCount, 0);
  if (nsm == 132) {
    cudaFuncSetAttribute(mega_kernel<true>, cudaFuncAttributeMaxDynamicSharedMemorySize, SMEM_BYTES);
    mega_kernel<true><<<132, 384, SMEM_BYTES>>>(P);
  } else {
    cudaFuncSetAttribute(mega_kernel<false>, cudaFuncAttributeMaxDynamicSharedMemorySize, SMEM_BYTES);
    mega_kernel<false><<<132, 384, SMEM_BYTES>>>(P);
  }
}
```
